```python
import torch

def _softmax(x, axis=-1):
    return torch.softmax(x, dim=axis)
def _gelu(x):
    return torch.nn.functional.gelu(x, approximate="tanh")
def _silu(x):
    return torch.nn.functional.silu(x)
def _sigmoid(x):
    return torch.sigmoid(x)
def _layernorm(x, axis=-1, eps=1e-5):
    m = x.mean(dim=axis, keepdim=True)
    v = x.var(dim=axis, keepdim=True, unbiased=False)
    return (x - m) / torch.sqrt(v + eps)
def _scatter_add(tgt, idx, src, axis=0):
    return tgt.clone().index_add_(axis, idx, src)
def _segment_sum(src, seg, n):
    out = torch.zeros((n,) + src.shape[1:], dtype=src.dtype)
    return out.index_add_(0, seg, src)
def _pad(x, pw):
    flat = tuple(v for pair in reversed(pw) for v in pair)
    return torch.nn.functional.pad(x, flat)

kernel_name = 'recurrent_scan__sliding_local_dilated__mixer_token_mlp__prompt'

def setup_inputs():

    _w = (lambda a: (lambda t: t.to(torch.bfloat16) if t.is_floating_point() else t)(torch.as_tensor(a)))
    def _A_setup():
        B, S, D = 1, 2048, 512
        return {
            "x": _w((lambda *s: torch.randn(*s, dtype=torch.bfloat16) * 0.05)(B, S, D)),
            "wqkv": _w((lambda *s: torch.randn(*s, dtype=torch.bfloat16) * 0.2)(D, 3 * D)),
            "wo": _w((lambda *s: torch.randn(*s, dtype=torch.bfloat16) * 0.2)(D, D)),
        }
    _A_in = _A_setup()

    def _B_setup():
        B, S, D, F = 1, 2048, 512, 1792
        return {
            "x": _w((lambda *s: torch.randn(*s, dtype=torch.bfloat16) * 0.05)(B, S, D)),
            "w1": _w((lambda *s: torch.randn(*s, dtype=torch.bfloat16) * 0.8)(S, F) * (S ** -0.5)),
            "b1": _w((lambda *s: torch.randn(*s, dtype=torch.bfloat16) * 12.8)(F) * 0.02),
            "w2": _w((lambda *s: torch.randn(*s, dtype=torch.bfloat16) * 0.8)(F, S) * (F ** -0.5)),
            "b2": _w((lambda *s: torch.randn(*s, dtype=torch.bfloat16) * 12.8)(S) * 0.02),
        }
    _B_in = _B_setup()

    return {
        "A_x": _A_in["x"],
        "A_wqkv": _A_in["wqkv"],
        "A_wo": _A_in["wo"],
        "B_x": _B_in["x"],
        "B_w1": _B_in["w1"],
        "B_b1": _B_in["b1"],
        "B_w2": _B_in["w2"],
        "B_b2": _B_in["b2"],
    }

def reference(A_x, A_wqkv, A_wo, B_x, B_w1, B_b1, B_w2, B_b2):
    def _A_ref(x, wqkv, wo):
        B, S, D = x.shape
        H = 32; Dh = D // H
        W, dil = 8, 2
        qkv = (lambda x, *d: x.permute(*d))((x @ wqkv).reshape(B, S, 3, H, Dh), 2, 0, 3, 1, 4)
        q, k, v = qkv[0], qkv[1], qkv[2]
        scale = Dh ** -0.5
        pos = torch.arange(S)
        off = torch.arange(W) * dil
        idx = pos[:, None] - off[None, :]
        mask = idx >= 0
        idx_c = torch.where(mask, idx, 0).reshape(-1)
        kg = k[:, :, idx_c, :].reshape(B, H, S, W, Dh)
        vg = v[:, :, idx_c, :].reshape(B, H, S, W, Dh)
        logits = torch.einsum("bhsd,bhswd->bhsw", q, kg) * scale
        logits = torch.where(mask[None, None, :, :], logits, -1e9)
        attn = _softmax(logits, axis=-1)
        o = torch.einsum("bhsw,bhswd->bhsd", attn, vg)
        return (lambda x, *d: x.permute(*d))(o, 0, 2, 1, 3).reshape(B, S, D) @ wo

    def _B_ref(x, w1, b1, w2, b2):
        B, S, D = x.shape
        h = _layernorm(x, axis=-1)
        u = torch.einsum("bsd,sf->bdf", h, w1) + b1
        u = _gelu(u)
        y = torch.einsum("bdf,fs->bds", u, w2) + b2
        return (lambda x, *d: x.permute(*d))(y, 0, 2, 1)

    x = A_x
    xn = _layernorm(x, axis=-1)
    s = _A_ref(xn, A_wqkv, A_wo)
    g = _silu(_B_ref(xn, B_w1, B_b1, B_w2, B_b2))
    return x + s * g
```

```cpp
#include <cuda_runtime.h>
#include <cuda.h>
#include <cuda_bf16.h>
#include <stdint.h>

namespace {

constexpr int S_ = 2048, D_ = 512, F_ = 1792;
#define KA_ 4

#define PF_FIRST 2
#define PF_LAST 33
#define PF_DELAY 3000
#define PF_NS 220
#define SPIN_NS 30
constexpr uint64_t WATCHDOG_NS = 2000000000ull;
#define PRIO 1
#define FIN 0
#define HOLDKB 0
#define WIN1 8
#define WIN2 (WIN1 + 2)
#define NWIN 3
#define PAUSE (WIN2 + 10)
#define ACT16 0
#define WIN3 (WIN2 + 2)
#define POLLDEPTH 1
#define POLL_NS 80
#define UGRP 0
#define HALO_NS 0
#define WINMIN 3
#define MEANFOLD 0
#define EPIROLL 0
constexpr int KA = KA_;
constexpr int NSLOT = 8;
constexpr int SLOT = 24576;
constexpr int OFF_R0 = NSLOT * SLOT;
constexpr int OFF_R1 = OFF_R0 + 16384;
constexpr int OFF_CS = OFF_R1 + 16384;
constexpr int OFF_BAR = OFF_CS + 768;
constexpr int BAR_FULL = OFF_BAR, BAR_FLAG = BAR_FULL + 64, BAR_X = BAR_FLAG + 40, BAR_DONE = BAR_X + 8, BAR_LN = BAR_X + 16, BAR_EMPTY = BAR_FULL + 128,
              BAR_RDY = BAR_EMPTY + 64, BAR_PUB = BAR_RDY + 8, BAR_OST = BAR_RDY + 16, BAR_GO = BAR_RDY + 24, OFF_ZERO = BAR_RDY + 32, OFF_EP = BAR_RDY + 48;
constexpr int SMEM_BYTES = OFF_BAR + 256;

struct __align__(1024) Scratch {
  uint32_t ctr[40 * 32];
  float2 stats[S_];
  float colpart[8][8][192];
  uint4 halo[128][8][32];
  __nv_bfloat16 h[S_ * D_];
  __nv_bfloat16 u[D_ * F_];
  __nv_bfloat16 o[S_ * D_];
};
__device__ Scratch g_s;

enum { M_W3, M_X3, M_W1, M_H, M_W2, M_U, M_WO, M_O2, M_O3, M_X2, M_OUT, NMAPS };
struct Maps {
  CUtensorMap m[NMAPS];
  uint8_t role[160];
};

__device__ __forceinline__ uint32_t smem_u32(const void* p) { return (uint32_t)__cvta_generic_to_shared(p); }
__device__ __forceinline__ void mbar_init(uint32_t bar, uint32_t cnt) {
  asm volatile("mbarrier.init.shared::cta.b64 [%0], %1;" ::"r"(bar), "r"(cnt) : "memory");
}
__device__ __forceinline__ void mbar_expect_tx(uint32_t bar, uint32_t bytes) {
  asm volatile("mbarrier.arrive.expect_tx.shared::cta.b64 _, [%0], %1;" ::"r"(bar), "r"(bytes) : "memory");
}
__device__ __forceinline__ void mbar_arrive(uint32_t bar) {
  asm volatile("mbarrier.arrive.shared::cta.b64 _, [%0];" ::"r"(bar) : "memory");
}
__device__ __forceinline__ void mbar_arrive_n(uint32_t bar, uint32_t n) {
  asm volatile("mbarrier.arrive.shared::cta.b64 _, [%0], %1;" ::"r"(bar), "r"(n) : "memory");
}
__device__ __forceinline__ void mbar_wait(uint32_t bar, uint32_t parity) {
  asm volatile("{\n.reg .pred p;\nLAB_WAIT:\nmbarrier.try_wait.parity.shared::cta.b64 p, [%0], %1;\n@!p bra LAB_WAIT;\n}" ::"r"(bar),
               "r"(parity)
               : "memory");
}
__device__ __forceinline__ uint32_t mbar_try(uint32_t bar, uint32_t parity) {
  uint32_t ok;
  asm volatile("{\n.reg .pred p;\nmbarrier.try_wait.parity.shared::cta.b64 p, [%1], %2;\nselp.b32 %0, 1, 0, p;\n}"
               : "=r"(ok) : "r"(bar), "r"(parity) : "memory");
  return ok;
}
__device__ __forceinline__ uint32_t mbar_test(uint32_t bar, uint32_t parity) {
  uint32_t ok;
  asm volatile("{\n.reg .pred p;\nmbarrier.test_wait.parity.shared::cta.b64 p, [%1], %2;\nselp.b32 %0, 1, 0, p;\n}"
               : "=r"(ok) : "r"(bar), "r"(parity) : "memory");
  return ok;
}
__device__ __forceinline__ bool elect_one() {
  uint32_t p;
  asm volatile("{\n.reg .pred P;\nelect.sync _|P, 0xffffffff;\nselp.b32 %0, 1, 0, P;\n}" : "=r"(p));
  return p;
}
__device__ __forceinline__ void tma3(uint32_t dst, const CUtensorMap* tm, uint32_t bar, int c0, int c1, int c2) {
  asm volatile(
      "cp.async.bulk.tensor.3d.shared::cluster.global.mbarrier::complete_tx::bytes [%0], [%1, {%3, %4, %5}], [%2];" ::"r"(dst),
      "l"(tm), "r"(bar), "r"(c0), "r"(c1), "r"(c2)
      : "memory");
}
__device__ __forceinline__ void tma3_st(const CUtensorMap* tm, uint32_t src, int c0, int c1, int c2) {
  asm volatile("cp.async.bulk.tensor.3d.global.shared::cta.bulk_group [%0, {%2, %3, %4}], [%1];" ::"l"(tm), "r"(src),
               "r"(c0), "r"(c1), "r"(c2)
               : "memory");
}
__device__ __forceinline__ void bulk_commit() { asm volatile("cp.async.bulk.commit_group;" ::: "memory"); }
__device__ __forceinline__ void bulk_wait0() { asm volatile("cp.async.bulk.wait_group 0;" ::: "memory"); }
__device__ __forceinline__ void l2_prefetch(const void* p, uint32_t bytes) {
  asm volatile("cp.async.bulk.prefetch.L2.global [%0], %1;" ::"l"(p), "r"(bytes) : "memory");
}
__device__ __forceinline__ void prefetch_map(const CUtensorMap* tm) {
  asm volatile("prefetch.tensormap [%0];" ::"l"(tm) : "memory");
}
__device__ __forceinline__ void fence_async_smem() { asm volatile("fence.proxy.async.shared::cta;" ::: "memory"); }
__device__ __forceinline__ void fence_async_global() { asm volatile("fence.proxy.async.global;" ::: "memory"); }
__device__ __forceinline__ void wg_fence() { asm volatile("wgmma.fence.sync.aligned;" ::: "memory"); }
__device__ __forceinline__ void wg_commit() { asm volatile("wgmma.commit_group.sync.aligned;" ::: "memory"); }
template <int N>
__device__ __forceinline__ void wg_wait() { asm volatile("wgmma.wait_group.sync.aligned %0;" ::"n"(N) : "memory"); }
template <int N>
__device__ __forceinline__ void fence_regs(float (&d)[N]) {
#pragma unroll
  for (int i = 0; i < N; i++) asm volatile("" : "+f"(d[i])::"memory");
}
template <int N>
__device__ __forceinline__ void undef_regs(float (&d)[N]) {
#pragma unroll
  for (int i = 0; i < N; i++) asm volatile("" : "=f"(d[i]));
}
__device__ __forceinline__ uint32_t ldg_nc(const void* p) {
  uint32_t v;
  asm volatile("ld.global.nc.u32 %0, [%1];" : "=r"(v) : "l"(p));
  return v;
}
template <int ID, int N>
__device__ __forceinline__ void bar_sync() { asm volatile("bar.sync %0, %1;" ::"n"(ID), "n"(N) : "memory"); }
template <int ID>
__device__ __forceinline__ void bar_arrive_after(uint32_t n, uint32_t dep, uint32_t zero) {
  asm volatile("bar.arrive %0, %1;" ::"n"(ID), "r"(n + (dep & zero)) : "memory");
}
template <int ID, int N>
__device__ __forceinline__ uint32_t bar_all(uint32_t v) {
  uint32_t r;
  asm volatile("{\n.reg .pred p, q;\nsetp.ne.u32 p, %1, 0;\nbar.red.and.pred q, %2, %3, p;\nselp.b32 %0, 1, 0, q;\n}"
               : "=r"(r) : "r"(v), "n"(ID), "n"(N) : "memory");
  return r;
}
template <int ID, int N>
__device__ __forceinline__ void bar_arrive() { asm volatile("bar.arrive %0, %1;" ::"n"(ID), "n"(N) : "memory"); }
__device__ __forceinline__ uint32_t dlo(uint32_t addr) { return (addr >> 4) | (512u << 16); }
__device__ __forceinline__ uint64_t dsc(uint32_t lo) {
  uint64_t d;
  asm("mov.b64 %0, {%1, %2};" : "=l"(d) : "r"(lo), "r"(0x40000040u));
  return d;
}
__device__ __forceinline__ uint32_t ld_relaxed(const uint32_t* p) {
  uint32_t v;
  asm volatile("ld.relaxed.gpu.global.u32 %0, [%1];" : "=r"(v) : "l"(p) : "memory");
  return v;
}
__device__ __forceinline__ void red_release(uint32_t* p, uint32_t v) {
  asm volatile("red.release.gpu.global.add.u32 [%0], %1;" ::"l"(p), "r"(v) : "memory");
}
__device__ __forceinline__ uint32_t ld_acquire(const uint32_t* p) {
  uint32_t v;
  asm volatile("ld.acquire.gpu.global.u32 %0, [%1];" : "=r"(v) : "l"(p) : "memory");
  return v;
}
__device__ __forceinline__ void red_relaxed(uint32_t* p, uint32_t v) {
  asm volatile("red.relaxed.gpu.global.add.u32 [%0], %1;" ::"l"(p), "r"(v) : "memory");
}
__device__ __forceinline__ void bulk_st(void* dst, uint32_t src, uint32_t bytes) {
  asm volatile("cp.async.bulk.global.shared::cta.bulk_group [%0], [%1], %2;" ::"l"(dst), "r"(src), "r"(bytes) : "memory");
}
__device__ __forceinline__ void wait_ctr(const uint32_t* p, uint32_t target) {
  while ((int32_t)(ld_acquire(p) - target) < 0) { }
}
__device__ __forceinline__ uint64_t globaltime() {
  uint64_t v;
  asm volatile("mov.u64 %0, %%globaltimer;" : "=l"(v));
  return v;
}
__device__ __forceinline__ uint32_t pack_bf16(float lo, float hi) {
  uint32_t r;
  asm("cvt.rn.bf16x2.f32 %0, %1, %2;" : "=r"(r) : "f"(hi), "f"(lo));
  return r;
}
__device__ __forceinline__ float bf_lo(uint32_t v) { return __uint_as_float(v << 16); }
__device__ __forceinline__ float bf_hi(uint32_t v) { return __uint_as_float(v & 0xffff0000u); }
__device__ __forceinline__ float bf_round(float x) { return bf_hi(pack_bf16(0.f, x)); }
__device__ __forceinline__ float ex2(float x) {
  float r;
  asm("ex2.approx.ftz.f32 %0, %1;" : "=f"(r) : "f"(x));
  return r;
}
__device__ __forceinline__ float rcp(float x) {
  float r;
  asm("rcp.approx.ftz.f32 %0, %1;" : "=f"(r) : "f"(x));
  return r;
}
__device__ __forceinline__ float tanh_fast(float x) {
  float r;
  asm("tanh.approx.f32 %0, %1;" : "=f"(r) : "f"(x));
  return r;
}
__device__ __forceinline__ void tanh_poly16(float h0, float h1, uint32_t a2, uint32_t b2, float& t0, float& t1) {
  asm("{\n.reg .b32 h, s, z;\n.reg .f16 l, u;\n"
      "cvt.rn.satfinite.f16x2.f32 h, %3, %2;\n"
      "min.xorsign.abs.f16x2 h, h, %6;\n"
      "mul.rn.f16x2 s, h, h;\nfma.rn.f16x2 s, s, %5, %4;\nmul.rn.f16x2 z, h, s;\n"
      "tanh.approx.f16x2 z, z;\nmov.b32 {l, u}, z;\ncvt.f32.f16 %0, l;\ncvt.f32.f16 %1, u;\n}"
      : "=f"(t0), "=f"(t1) : "f"(h0), "f"(h1), "r"(a2), "r"(b2), "r"(0x58005800u));
}
__device__ __forceinline__ uint32_t movm(uint32_t a) {
  uint32_t d;
  asm volatile("movmatrix.sync.aligned.m8n8.trans.b16 %0, %1;" : "=r"(d) : "r"(a));
  return d;
}
__device__ __forceinline__ void stsm4(uint32_t addr, uint32_t a, uint32_t b, uint32_t c, uint32_t d) {
  asm volatile("stmatrix.sync.aligned.m8n8.x4.shared.b16 [%0], {%1, %2, %3, %4};" ::"r"(addr), "r"(a), "r"(b), "r"(c), "r"(d)
               : "memory");
}
__device__ __forceinline__ void stsm4t(uint32_t addr, uint32_t a, uint32_t b, uint32_t c, uint32_t d) {
  asm volatile("stmatrix.sync.aligned.m8n8.x4.trans.shared.b16 [%0], {%1, %2, %3, %4};" ::"r"(addr), "r"(a), "r"(b), "r"(c),
               "r"(d)
               : "memory");
}
__device__ __forceinline__ void ldsm4t(uint32_t addr, uint32_t& a, uint32_t& b, uint32_t& c, uint32_t& d) {
  asm volatile("ldmatrix.sync.aligned.m8n8.x4.trans.shared.b16 {%0, %1, %2, %3}, [%4];"
               : "=r"(a), "=r"(b), "=r"(c), "=r"(d)
               : "r"(addr)
               : "memory");
}
__device__ __forceinline__ void sts128(uint32_t addr, uint32_t a, uint32_t b, uint32_t c, uint32_t d) {
  asm volatile("st.shared.v4.b32 [%0], {%1, %2, %3, %4};" ::"r"(addr), "r"(a), "r"(b), "r"(c), "r"(d) : "memory");
}
__device__ __forceinline__ void lds128(uint32_t addr, uint32_t& a, uint32_t& b, uint32_t& c, uint32_t& d) {
  asm volatile("ld.shared.v4.b32 {%0, %1, %2, %3}, [%4];" : "=r"(a), "=r"(b), "=r"(c), "=r"(d) : "r"(addr) : "memory");
}
__device__ __forceinline__ void mma16816(float (&c)[4], uint32_t a0, uint32_t a1, uint32_t a2, uint32_t a3, uint32_t b0,
                                         uint32_t b1) {
  asm volatile("mma.sync.aligned.m16n8k16.row.col.f32.bf16.bf16.f32 {%0,%1,%2,%3}, {%4,%5,%6,%7}, {%8,%9}, {%0,%1,%2,%3};"
               : "+f"(c[0]), "+f"(c[1]), "+f"(c[2]), "+f"(c[3])
               : "r"(a0), "r"(a1), "r"(a2), "r"(a3), "r"(b0), "r"(b1));
}
__device__ __forceinline__ void mma16816z(float (&c)[4], uint32_t a0, uint32_t a1, uint32_t a2, uint32_t a3, uint32_t b0,
                                          uint32_t b1, const uint32_t (&z)[4]) {
  asm volatile("mma.sync.aligned.m16n8k16.row.col.f32.bf16.bf16.f32 {%0,%1,%2,%3}, {%4,%5,%6,%7}, {%8,%9}, {%10,%11,%12,%13};"
               : "=f"(c[0]), "=f"(c[1]), "=f"(c[2]), "=f"(c[3])
               : "r"(a0), "r"(a1), "r"(a2), "r"(a3), "r"(b0), "r"(b1), "f"(__uint_as_float(z[0])), "f"(__uint_as_float(z[1])),
                 "f"(__uint_as_float(z[2])), "f"(__uint_as_float(z[3])));
}
__device__ __forceinline__ uint32_t hmax2_bf(uint32_t a, uint32_t b) {
  uint32_t r;
  asm("max.bf16x2 %0, %1, %2;" : "=r"(r) : "r"(a), "r"(b));
  return r;
}
__device__ __forceinline__ void mma1688z(float (&c)[4], uint32_t a0, uint32_t a1, uint32_t b0, const uint32_t (&z)[4]) {
  asm volatile("mma.sync.aligned.m16n8k8.row.col.f32.bf16.bf16.f32 {%0,%1,%2,%3}, {%4,%5}, {%6}, {%7,%8,%9,%10};"
               : "=f"(c[0]), "=f"(c[1]), "=f"(c[2]), "=f"(c[3])
               : "r"(a0), "r"(a1), "r"(b0), "f"(__uint_as_float(z[0])), "f"(__uint_as_float(z[1])), "f"(__uint_as_float(z[2])),
                 "f"(__uint_as_float(z[3])));
}
__device__ __forceinline__ void mma1688(float (&c)[4], uint32_t a0, uint32_t a1, uint32_t b0) {
  asm volatile("mma.sync.aligned.m16n8k8.row.col.f32.bf16.bf16.f32 {%0,%1,%2,%3}, {%4,%5}, {%6}, {%0,%1,%2,%3};"
               : "+f"(c[0]), "+f"(c[1]), "+f"(c[2]), "+f"(c[3])
               : "r"(a0), "r"(a1), "r"(b0));
}
__device__ __forceinline__ uint32_t hmul2_bf(uint32_t a, uint32_t b) {
  uint32_t r;
  asm("mul.rn.bf16x2 %0, %1, %2;" : "=r"(r) : "r"(a), "r"(b));
  return r;
}
__device__ __forceinline__ uint32_t hsub2_bf(uint32_t a, uint32_t b) {
  uint32_t r;
  asm("sub.rn.bf16x2 %0, %1, %2;" : "=r"(r) : "r"(a), "r"(b));
  return r;
}
__device__ __forceinline__ uint32_t hfma2_bf(uint32_t a, uint32_t b, uint32_t c) {
  uint32_t r;
  asm("fma.rn.bf16x2 %0, %1, %2, %3;" : "=r"(r) : "r"(a), "r"(b), "r"(c));
  return r;
}
__device__ __forceinline__ float sqrt_fast(float x) {
  float r;
  asm("sqrt.approx.ftz.f32 %0, %1;" : "=f"(r) : "f"(x));
  return r;
}
__device__ __forceinline__ uint32_t hadd2_bf(uint32_t a, uint32_t b) {
  uint32_t r;
  asm("add.rn.bf16x2 %0, %1, %2;" : "=r"(r) : "r"(a), "r"(b));
  return r;
}

template <int TA, int TB>
__device__ __forceinline__ void wgmma_n128(float (&d)[64], uint64_t da, uint64_t db, int sd) {
  asm volatile(
      "{\n.reg .pred p;\nsetp.ne.b32 p, %66, 0;\n"
      "wgmma.mma_async.sync.aligned.m64n128k16.f32.bf16.bf16 {"
      "%0, %1, %2, %3, %4, %5, %6, %7, %8, %9, %10, %11, %12, %13, %14, %15, %16, %17, %18, %19, %20, %21, %22, %23, "
      "%24, %25, %26, %27, %28, %29, %30, %31, %32, %33, %34, %35, %36, %37, %38, %39, %40, %41, %42, %43, %44, %45, "
      "%46, %47, %48, %49, %50, %51, %52, %53, %54, %55, %56, %57, %58, %59, %60, %61, %62, %63"
      "}, %64, %65, p, 1, 1, %67, %68;\n}\n"
      :
      "+f"(d[0]), "+f"(d[1]), "+f"(d[2]), "+f"(d[3]), "+f"(d[4]), "+f"(d[5]), "+f"(d[6]), "+f"(d[7]), "+f"(d[8]),
      "+f"(d[9]), "+f"(d[10]), "+f"(d[11]), "+f"(d[12]), "+f"(d[13]), "+f"(d[14]), "+f"(d[15]), "+f"(d[16]),
      "+f"(d[17]), "+f"(d[18]), "+f"(d[19]), "+f"(d[20]), "+f"(d[21]), "+f"(d[22]), "+f"(d[23]), "+f"(d[24]),
      "+f"(d[25]), "+f"(d[26]), "+f"(d[27]), "+f"(d[28]), "+f"(d[29]), "+f"(d[30]), "+f"(d[31]), "+f"(d[32]),
      "+f"(d[33]), "+f"(d[34]), "+f"(d[35]), "+f"(d[36]), "+f"(d[37]), "+f"(d[38]), "+f"(d[39]), "+f"(d[40]),
      "+f"(d[41]), "+f"(d[42]), "+f"(d[43]), "+f"(d[44]), "+f"(d[45]), "+f"(d[46]), "+f"(d[47]), "+f"(d[48]),
      "+f"(d[49]), "+f"(d[50]), "+f"(d[51]), "+f"(d[52]), "+f"(d[53]), "+f"(d[54]), "+f"(d[55]), "+f"(d[56]),
      "+f"(d[57]), "+f"(d[58]), "+f"(d[59]), "+f"(d[60]), "+f"(d[61]), "+f"(d[62]), "+f"(d[63])
      : "l"(da), "l"(db), "r"(sd), "n"(TA), "n"(TB));
}

template <int TA, int TB>
__device__ __forceinline__ void wgmma_n192(float (&d)[96], uint64_t da, uint64_t db, int sd) {
  asm volatile(
      "{\n.reg .pred p;\nsetp.ne.b32 p, %98, 0;\n"
      "wgmma.mma_async.sync.aligned.m64n192k16.f32.bf16.bf16 {"
      "%0, %1, %2, %3, %4, %5, %6, %7, %8, %9, %10, %11, %12, %13, %14, %15, %16, %17, %18, %19, %20, %21, %22, %23, "
      "%24, %25, %26, %27, %28, %29, %30, %31, %32, %33, %34, %35, %36, %37, %38, %39, %40, %41, %42, %43, %44, %45, "
      "%46, %47, %48, %49, %50, %51, %52, %53, %54, %55, %56, %57, %58, %59, %60, %61, %62, %63, %64, %65, %66, %67, "
      "%68, %69, %70, %71, %72, %73, %74, %75, %76, %77, %78, %79, %80, %81, %82, %83, %84, %85, %86, %87, %88, %89, "
      "%90, %91, %92, %93, %94, %95"
      "}, %96, %97, p, 1, 1, %99, %100;\n}\n"
      :
      "+f"(d[0]), "+f"(d[1]), "+f"(d[2]), "+f"(d[3]), "+f"(d[4]), "+f"(d[5]), "+f"(d[6]), "+f"(d[7]), "+f"(d[8]),
      "+f"(d[9]), "+f"(d[10]), "+f"(d[11]), "+f"(d[12]), "+f"(d[13]), "+f"(d[14]), "+f"(d[15]), "+f"(d[16]),
      "+f"(d[17]), "+f"(d[18]), "+f"(d[19]), "+f"(d[20]), "+f"(d[21]), "+f"(d[22]), "+f"(d[23]), "+f"(d[24]),
      "+f"(d[25]), "+f"(d[26]), "+f"(d[27]), "+f"(d[28]), "+f"(d[29]), "+f"(d[30]), "+f"(d[31]), "+f"(d[32]),
      "+f"(d[33]), "+f"(d[34]), "+f"(d[35]), "+f"(d[36]), "+f"(d[37]), "+f"(d[38]), "+f"(d[39]), "+f"(d[40]),
      "+f"(d[41]), "+f"(d[42]), "+f"(d[43]), "+f"(d[44]), "+f"(d[45]), "+f"(d[46]), "+f"(d[47]), "+f"(d[48]),
      "+f"(d[49]), "+f"(d[50]), "+f"(d[51]), "+f"(d[52]), "+f"(d[53]), "+f"(d[54]), "+f"(d[55]), "+f"(d[56]),
      "+f"(d[57]), "+f"(d[58]), "+f"(d[59]), "+f"(d[60]), "+f"(d[61]), "+f"(d[62]), "+f"(d[63]), "+f"(d[64]),
      "+f"(d[65]), "+f"(d[66]), "+f"(d[67]), "+f"(d[68]), "+f"(d[69]), "+f"(d[70]), "+f"(d[71]), "+f"(d[72]),
      "+f"(d[73]), "+f"(d[74]), "+f"(d[75]), "+f"(d[76]), "+f"(d[77]), "+f"(d[78]), "+f"(d[79]), "+f"(d[80]),
      "+f"(d[81]), "+f"(d[82]), "+f"(d[83]), "+f"(d[84]), "+f"(d[85]), "+f"(d[86]), "+f"(d[87]), "+f"(d[88]),
      "+f"(d[89]), "+f"(d[90]), "+f"(d[91]), "+f"(d[92]), "+f"(d[93]), "+f"(d[94]), "+f"(d[95])
      : "l"(da), "l"(db), "r"(sd), "n"(TA), "n"(TB));
}

#define PROFV(i, v) do { } while (0)
#define WAITT(acc, stmt) do { stmt; } while (0)
#define PROF(i) do { } while (0)

constexpr uint32_t N_G1 = 2 * KA, N_QB = 2 * KA + 32, N_G2 = 48, N_OP = 76, N_END = 84;
#define NPRE_ 2
constexpr uint32_t NPRE = NPRE_;

__device__ __forceinline__ uint32_t full_bar(uint32_t sb, uint32_t n) { return sb + BAR_FULL + 8 * (n & 7); }
__device__ __forceinline__ uint32_t empty_bar(uint32_t sb, uint32_t n) { return sb + BAR_EMPTY + 8 * (n & 7); }
__device__ __forceinline__ uint32_t slot_addr(uint32_t sb, uint32_t n) { return sb + (n & 7) * SLOT; }

__global__ void __launch_bounds__(512, 1)
fused_kernel(const __grid_constant__ Maps mp, const __nv_bfloat16* __restrict__ x, const __nv_bfloat16* __restrict__ wqkv,
             const __nv_bfloat16* __restrict__ wo, const __nv_bfloat16* __restrict__ w1, const __nv_bfloat16* __restrict__ b1,
             const __nv_bfloat16* __restrict__ w2, const __nv_bfloat16* __restrict__ b2, __nv_bfloat16* __restrict__ out) {
  extern __shared__ __align__(1024) uint8_t smem_raw[];
  constexpr uint32_t sb = 1024;
  const int lane = threadIdx.x & 31;
  const int pwarp = __shfl_sync(0xffffffffu, threadIdx.x >> 5, 0);
  if (pwarp >= 14) prefetch_map(&mp.m[pwarp - 14]);

  uint32_t smid, nsm;
  asm volatile("mov.u32 %0, %%smid;" : "=r"(smid));
  asm volatile("mov.u32 %0, %%nsmid;" : "=r"(nsm));
  if (nsm != 132) smid = blockIdx.x;
  const uint32_t role = mp.role[smid];
  const int ta = role & 7;
  const int tb = role >> 3;
  const bool g1_active = tb < 14;
  uint32_t* const ctr = g_s.ctr;

  if (pwarp >= 14 && role != 255 && elect_one()) {
    const int q = pwarp - 14;
#pragma unroll
    for (int s = 0; s < 4; s++) mbar_init(sb + BAR_FULL + 8 * q + 16 * s, 1);
    if (q) mbar_init(sb + BAR_LN, 1);
    asm volatile("fence.mbarrier_init.release.cluster;" ::: "memory");
    if (q) {
      mbar_expect_tx(sb + BAR_LN, 16384);
      asm volatile("cp.async.bulk.shared::cluster.global.mbarrier::complete_tx::bytes [%0], [%1], %2, [%3];" ::"r"(sb + OFF_R1),
                   "l"(x + role * 16 * D_), "r"(16384), "r"(sb + BAR_LN) : "memory");
    }
#pragma unroll
    for (int s = 0; s < NPRE / 2; s++) {
      mbar_expect_tx(full_bar(sb, 2 * s + q), q ? 16384 : 24576);
      tma3(slot_addr(sb, 2 * s + q), &mp.m[q], full_bar(sb, 2 * s + q), q ? s * 64 : ta * 64, q ? tb >> 3 : s * 64, q ? (tb & 7) * 128 : 0);
    }
  }
  const int warp = pwarp < 4 ? pwarp + 8 : pwarp < 12 ? pwarp - 4 : pwarp;
  const int tid = warp * 32 + lane;
  const int g = lane >> 2, t = lane & 3;

  if (role == 255) {
    if (tid == 0) {
      uint32_t ep = ld_relaxed(ctr);
      red_release(ctr + 32, 1);
      for (int n = 0; (int32_t)(ld_acquire(ctr + 32) - (ep + 1) * 132) < 0; n++) {
        __nanosleep(200);
        if (n > (1 << 22)) __trap();
      }
    }
    return;
  }

  if (warp >= 12) {
    uint32_t ep = 0;
    if (warp == 14) ep = ld_relaxed(ctr);
    if (warp < 14 && elect_one()) {
      if (warp == 12) {
#pragma unroll
        for (int s = 0; s < 7; s++) mbar_init(sb + BAR_FLAG + 8 * s, 1);
      } else {
#pragma unroll
        for (int s = 0; s < 9; s++) mbar_init(sb + BAR_EMPTY + 8 * s, 8);
        mbar_init(sb + BAR_PUB, 4);
        mbar_init(sb + BAR_OST, 2);
        mbar_init(sb + BAR_GO, 2);
        sts128(sb + OFF_ZERO, 0, 0, 0, 0);
      }
      asm volatile("fence.mbarrier_init.release.cluster;" ::: "memory");
    }
    bar_sync<10, 128>();
    bar_arrive<0, 512>();
    asm volatile("setmaxnreg.dec.sync.aligned.u32 40;");
    if (warp < 14) {
      const int q = warp - 12;
      uint32_t n = NPRE + q;
#pragma unroll 1
      for (int phase = 0; phase < 6; phase++) {
        const uint32_t nend = (uint32_t)(((uint64_t)N_END << 40 | (uint64_t)N_OP << 32 | (N_G2 + 14) << 24 | N_G2 << 16 | N_QB << 8 | N_G1) >> (8 * phase)) & 0xff;
        int mw = M_W2, w0 = 0, wk = q * 128 + (phase - 3) * 64, w2c = tb * 2, dk = 256;
        uint32_t bytes = 24576, offw = 8192, flag = sb + BAR_FLAG + 8 * (phase - 1);
        if (phase == 1) { mw = M_W1; flag = sb + BAR_FLAG; if (!g1_active) n += 32; }
        if (phase == 5) { mw = M_WO; w0 = ta * 64; w2c = 0; offw = 0; }
        if (phase == 1 || phase == 5) { wk = q * 64; dk = 128; }
        if (phase == 0 || phase == 2) {
          mw = M_W3 + q; w0 = ta * 64; wk = phase ? KA * 64 : NPRE * 32; w2c = 0; dk = 64; offw = 0; flag = 0;
          if (q) bytes = 16384;
        }
        const CUtensorMap* tm = &mp.m[mw];
        uint32_t na = flag ? n : 1000;
        int ak = wk;
        bool go = !flag;
#pragma unroll 1
        while (n < nend || na < nend) {
          if (n < nend && (go || mbar_test(empty_bar(sb, n), ((n >> 3) & 1) ^ 1))) {
            mbar_wait(empty_bar(sb, n), ((n >> 3) & 1) ^ 1);
            if (elect_one()) {
              mbar_expect_tx(full_bar(sb, n), bytes);
              const bool xt = mw == M_X3;
              tma3(slot_addr(sb, n) + offw, tm, full_bar(sb, n), xt ? wk : w0, xt ? tb >> 3 : wk, xt ? (tb & 7) * 128 : w2c);
            }
            __syncwarp();
            wk += dk;
            n += 2;
          }
          if (!go) {
            go = mbar_test(flag, 0);
            if (go) fence_async_global(); else __nanosleep(SPIN_NS);
          }
          if (go) {
#pragma unroll 1
            for (; na < n; na += 2) {
              if (elect_one())
                tma3(slot_addr(sb, na) + (8192 - offw), tm + 1, full_bar(sb, na), phase == 5 ? ak : ta * 64, phase == 5 ? tb * 128 : ak, 0);
              __syncwarp();
              ak += dk;
            }
          }
        }
      }
    } else if (lane == 0) {
      if (warp == 14) {
        asm volatile("st.shared.u32 [%0], %1;" ::"r"(sb + OFF_EP), "r"(ep) : "memory");
#pragma unroll 1
        for (int i = M_W1; i < NMAPS; i++) prefetch_map(&mp.m[i]);
        mbar_wait(sb + BAR_PUB, 0);
        red_relaxed(ctr + 32, 1);
        PROF(5);
#pragma unroll 1
        for (int i = 0; i < 5; i++) {
          wait_ctr(ctr + 32 * (i ? 8 * i + (i == 4 ? tb >> 1 : i == 1 ? ta : ta >> UGRP) : 1),
                   (ep + 1) * ((uint32_t)((UGRP ? 0x2038380284ull : 0x200E0E0284ull) >> (8 * i)) & 0xff));
          mbar_arrive(sb + BAR_FLAG + 8 * i);
          PROF(i == 0 ? 1 : i == 1 ? 42 : i == 2 ? 2 : i == 3 ? 43 : 3);
        }
      } else {
        if (smem_u32(smem_raw) != sb) __trap();
        const uint64_t t0 = globaltime();
        while (!mbar_try(sb + BAR_DONE, 0))
          if (globaltime() - t0 > WATCHDOG_NS) __trap();
      }
    }
  } else if (warp >= 8) {
    const int w = warp - 8, t128 = tid - 256;
    {
      uint32_t v[32];
      const int lr = w * 4 + (g & 3);
      const uint32_t eo = lr * D_ + (g >> 2) * 256 + t * 8;
      bar_sync<0, 512>();
      mbar_wait(sb + BAR_LN, 0);
      if (t128 == 0) PROF(40);
#pragma unroll
      for (int i = 0; i < 8; i++) lds128(sb + OFF_R1 + (eo + i * 32) * 2, v[4 * i], v[4 * i + 1], v[4 * i + 2], v[4 * i + 3]);
      float cs[2][4], q0[2][4], q1[2][4];
#pragma unroll
      for (int r = 0; r < 2; r++)
#pragma unroll
        for (int c = 0; c < 4; c++) cs[r][c] = q0[r][c] = q1[r][c] = 0.f;
#pragma unroll
      for (int k = 0; k < 32; k += 2) {
        const int r = (k >> 1) & 1;
        if (r == 0) mma16816(cs[(k >> 2) & 1], v[k], v[k + 1], v[k + 2], v[k + 3], 0x3F803F80u, 0x3F803F80u);
        mma1688(q0[r], v[k], v[k + 1], v[k]);
        mma1688(q1[r], v[k], v[k + 1], v[k + 1]);
      }
      float sum = (cs[0][0] + cs[0][2]) + (cs[1][0] + cs[1][2]);
      float sq = (g & 1) ? (q0[0][1] + q1[0][3]) + (q0[1][1] + q1[1][3]) : (q0[0][0] + q1[0][2]) + (q0[1][0] + q1[1][2]);
      sq = __shfl_sync(0xffffffffu, sq, (lane & 28) | (g >> 1));
      sum += __shfl_xor_sync(0xffffffffu, sum, 16);
      sq += __shfl_xor_sync(0xffffffffu, sq, 16);
      if (t128 == 0) PROF(4);
      const float m = sum * (1.f / D_);
      const float var = fmaxf(fmaf(-m, m, sq * (1.f / D_)), 0.f);
      const uint32_t mb2 = pack_bf16(m, m);
      const float inv = rcp(bf_round(sqrt_fast(bf_round(bf_round(var) + 1e-5f))));
      const float inv2 = rcp(bf_round(sqrt_fast(bf_round(bf_round(var * inv * inv) + 1e-5f))));
      const float sc = inv * inv2, sh = (bf_lo(mb2) - m) * sc;
      const uint32_t sh2 = pack_bf16(sh, sh), sch = pack_bf16(sc, sc);
      const float scl = sc - bf_lo(sch);
      const uint32_t scl2 = pack_bf16(scl, scl);
      if (lane < 16 && t == 0)
        asm volatile("st.shared.v2.f32 [%0], {%1, %2};" ::"r"(sb + OFF_R0 + lr * 8), "f"(bf_lo(mb2)), "f"(inv) : "memory");
#pragma unroll
      for (int i = 0; i < 8; i++) {
        uint32_t o[4];
#pragma unroll
        for (int k = 0; k < 4; k++) {
          const uint32_t cc = hsub2_bf(v[4 * i + k], mb2);
          o[k] = hfma2_bf(cc, sch, hfma2_bf(cc, scl2, sh2));
        }
        sts128(sb + OFF_R1 + (eo + i * 32) * 2, o[0], o[1], o[2], o[3]);
      }
      if (t128 == 0) PROF(25);
      fence_async_smem();
      bar_arrive<9, 384>();
      __syncwarp();
      if (lane == 0) {
        if (w == 0) PROF(26);
        bulk_st(g_s.h + (size_t)(role * 16 + w * 4) * D_, sb + OFF_R1 + w * 4096, 4096);
        bulk_st(g_s.stats + role * 16 + w * 4, sb + OFF_R0 + w * 32, 32);
        bulk_commit();
        bulk_wait0();
        mbar_arrive(sb + BAR_PUB);
      }
      bar_sync<1, 128>();
    }
    const uint32_t taddr = sb + OFF_R0 + ((lane >> 4) * 8 + (lane & 7)) * 128 + (((2 * w + ((lane >> 3) & 1)) ^ (lane & 7)) << 4);
    if (!g1_active) {
      float a[8] = {0.f, 0.f, 0.f, 0.f, 0.f, 0.f, 0.f, 0.f};
      if (lane < 24) {
        const uint4* pw = (const uint4*)(wqkv + (size_t)((tb - 14) * 256 + w * 64) * (3 * D_) + (lane >> 3) * D_ + ta * 64) + (lane & 7);
#pragma unroll 16
        for (int r = 0; r < 64; r++) {
          const uint4 q = __ldg(pw + r * (3 * D_ / 8));
          a[0] += bf_lo(q.x); a[1] += bf_hi(q.x); a[2] += bf_lo(q.y); a[3] += bf_hi(q.y);
          a[4] += bf_lo(q.z); a[5] += bf_hi(q.z); a[6] += bf_lo(q.w); a[7] += bf_hi(q.w);
        }
        const uint32_t dst = sb + OFF_R0 + 2048 + w * 768 + lane * 32;
        sts128(dst, __float_as_uint(a[0]), __float_as_uint(a[1]), __float_as_uint(a[2]), __float_as_uint(a[3]));
        sts128(dst + 16, __float_as_uint(a[4]), __float_as_uint(a[5]), __float_as_uint(a[6]), __float_as_uint(a[7]));
      }
      fence_async_smem();
      bar_sync<1, 128>();
      if (t128 == 0) {
        bulk_st(&g_s.colpart[ta][(tb - 14) * 4][0], sb + OFF_R0 + 2048, 3072);
        bulk_commit();
        bulk_wait0();
        red_relaxed(ctr + 32 * (8 + ta), 1);
      }
      __syncwarp();
      bar_sync<11, 384>();
      bar_arrive<2, 384>();
      bar_arrive<8, 384>();
    }
#pragma unroll 1
    for (int ph = g1_active ? 0 : 1; ph < 2; ph++) {
      uint32_t bh[16];
      {
        const uint32_t* bp = (const uint32_t*)((ph ? b2 : b1) + tb * 128) + t;
#pragma unroll
        for (int j = 0; j < 16; j++) bh[j] = ldg_nc(bp + 4 * j);
      }
      float acc[64];
      undef_regs(acc);
      long long wsum = 0;
      (void)wsum;
      const uint32_t n0 = ph ? N_G2 : N_G1, n1 = ph ? N_OP : N_QB;
      bar_sync<11, 384>();
      uint32_t win = 0;
      mbar_wait(full_bar(sb, n0), (n0 >> 3) & 1);
      if (t128 == 0) PROF(6 + 4 * ph);
#pragma unroll 1
      for (uint32_t n = n0; n < n1; n++) {
        const uint32_t a = dlo(slot_addr(sb, n));
        wg_fence();
        wgmma_n128<1, 1>(acc, dsc(a), dsc(a + 512), n != n0);
        const uint32_t ready = mbar_test(full_bar(sb, n + 1), ((n + 1) >> 3) & 1);
        wgmma_n128<1, 1>(acc, dsc(a + 128), dsc(a + 640), 1);
        wg_commit();
        wg_wait<1>();
        if (n != n0 && lane == 0) mbar_arrive_n(empty_bar(sb, n - 1), 2);
        const bool open = n == N_G2 + WIN1 || n == N_G2 + WIN2 || (NWIN == 3 && n == N_G2 + WIN3);
        wgmma_n128<1, 1>(acc, dsc(a + 256), dsc(a + 768), 1);
        wgmma_n128<1, 1>(acc, dsc(a + 384), dsc(a + 896), 1);
        wg_commit();
        if (n == n1 - 1) {
          if (ph == 0) bar_arrive<2, 384>(); else bar_arrive<3, 256>();
        } else if (!ready) {
          WAITT(wsum, mbar_wait(full_bar(sb, n + 1), ((n + 1) >> 3) & 1));
        }
        if (open) {
          bar_arrive<13, 384>();
          bar_sync<14, 384>();
          win++;
        }
      }
#pragma unroll 1
      for (; win < (NWIN == 3 ? 3 : 2) * ph; win++) {
        bar_arrive<13, 384>();
        bar_sync<14, 384>();
      }
      wg_wait<0>();
      fence_regs(acc);
      if (lane == 0) mbar_arrive_n(empty_bar(sb, n1 - 1), 2);
      if (t128 == 0) { PROF(7 + 4 * ph); PROFV(34 + ph, wsum); }
      if (ph) mbar_wait(sb + BAR_OST, 0);
      const float ca = ph ? 1.f : 2.f * 0.7978845608028654f, cb = ph ? 0.f : 8.f * 0.7978845608028654f * 0.044715f;
#pragma unroll
      for (int hf = 0; hf < 2; hf++) {
#pragma unroll
        for (int k = 0; k < 4; k++) {
          uint32_t R[4];
#pragma unroll
          for (int i = 0; i < 4; i++) {
            const uint32_t bv = hmul2_bf(bh[2 * k + (i >> 1)], 0x3F003F00u);
            const float h0 = fmaf(acc[8 * k + 2 * i], 0.5f, bf_lo(bv)), h1 = fmaf(acc[8 * k + 2 * i + 1], 0.5f, bf_hi(bv));
            const float t0 = tanh_fast(h0 * fmaf(cb, h0 * h0, ca)), t1 = tanh_fast(h1 * fmaf(cb, h1 * h1, ca));
            R[i] = pack_bf16(fmaf(h0, t0, h0), fmaf(h1, t1, h1));
          }
          stsm4t(taddr + hf * 8192 + k * 2048, R[0], R[1], R[2], R[3]);
        }
        if (ph == 0) {
          fence_async_smem();
          bar_sync<1, 128>();
          if (t128 == 0) {
            if (hf == 0) PROF(8);
            tma3_st(&mp.m[M_U], sb + OFF_R0 + hf * 8192, ta * 64, tb * 128 + hf * 64, 0);
            bulk_commit();
            bulk_wait0();
            red_relaxed(ctr + 32 * (16 + 8 * hf + (ta >> UGRP)), 1);
            PROF(hf ? 33 : 9);
          }
          __syncwarp();
        }
#pragma unroll
        for (int i = 0; i < 32; i++) acc[i] = acc[32 + i];
#pragma unroll
        for (int i = 0; i < 8; i++) bh[i] = bh[8 + i];
      }
      if (ph == 0) {
        bar_arrive<8, 384>();
      } else {
        bar_arrive<4, 256>();
        if (t128 == 0) PROF(12);
      }
    }
  } else {
    bar_sync<0, 512>();
    asm volatile("setmaxnreg.inc.sync.aligned.u32 168;");
    const int wg = warp >> 2;
    float acc[96];
    undef_regs(acc);
    uint32_t n = 0, ep = 0;
    float r0 = 0.f, r1 = 0.f, mr0 = 0.f, mr1 = 0.f;
    (void)mr0; (void)mr1;
    uint32_t ready = 0;
#pragma unroll 1
    for (int kb = 0; kb < 8; kb++) {
      if (kb == HOLDKB) bar_sync<9, 384>();
      if (kb == KA) {
        if (tid == 0) PROF(17);
        mbar_wait(sb + BAR_FLAG + 8, 0);
        asm volatile("ld.shared.u32 %0, [%1];" : "=r"(ep) : "r"(sb + OFF_EP) : "memory");
        const int i0 = (tb & 7) * 128 + warp * 16 + g;
        const float2 s0 = __ldcg(&g_s.stats[2 * i0 + (tb >> 3)]), s1 = __ldcg(&g_s.stats[2 * (i0 + 8) + (tb >> 3)]);
        r0 = s0.y; r1 = s1.y;
        if (tid < 192) {
          float a = 0.f;
#pragma unroll
          for (int k = 0; k < 8; k++) a += __ldcg(&g_s.colpart[ta][k][tid]);
          asm volatile("st.shared.f32 [%0], %1;" ::"r"(sb + OFF_CS + tid * 4), "f"(a) : "memory");
        }
        mr0 = -s0.x * r0; mr1 = -s1.x * r1;
        bar_sync<2, 384>();
        if (tid == 128) {
          mbar_expect_tx(sb + BAR_X, 16384);
          tma3(sb + OFF_R1, &mp.m[M_X2], sb + BAR_X, ta * 64, tb * 128, 0);
        }
        __syncwarp();
        n = N_QB;
      }
      if (!ready) {
        mbar_wait(full_bar(sb, n), (n >> 3) & 1);
        mbar_wait(full_bar(sb, n + 1), (n >> 3) & 1);
      }
      if (kb == 0 && tid == 0) PROF(16);
      if (kb == KA && tid == 0) PROF(19);
      const bool last = kb == KA - 1 || kb == 7;
      const uint32_t a = dlo(slot_addr(sb, n + 1) + wg * 8192), b = dlo(slot_addr(sb, n));
      wg_fence();
      wgmma_n192<0, 1>(acc, dsc(a), dsc(b), kb != 0);
      ready = (uint32_t)!last & mbar_test(full_bar(sb, n + 2), ((n + 2) >> 3) & 1) & mbar_test(full_bar(sb, n + 3), ((n + 2) >> 3) & 1);
      wgmma_n192<0, 1>(acc, dsc(a + 2), dsc(b + 128), 1);
      wg_commit();
      wg_wait<1>();
      if (kb != 0 && kb != KA && lane == 0) { mbar_arrive(empty_bar(sb, n - 2)); mbar_arrive(empty_bar(sb, n - 1)); }
      wgmma_n192<0, 1>(acc, dsc(a + 4), dsc(b + 256), 1);
      wgmma_n192<0, 1>(acc, dsc(a + 6), dsc(b + 384), 1);
      wg_commit();
      if (last) {
        bar_arrive<11, 384>();
        wg_wait<0>();
        if (lane == 0) { mbar_arrive(empty_bar(sb, n)); mbar_arrive(empty_bar(sb, n + 1)); }
      }
      n += 2;
    }
    wg_wait<0>();
    fence_regs(acc);
    if (tid == 0) PROF(20);

    uint32_t P[24][2], H[16];
    auto fold = [&](int j) {
      float c0, c1;
      asm volatile("ld.shared.v2.f32 {%0, %1}, [%2];" : "=f"(c0), "=f"(c1) : "r"(sb + OFF_CS + (8 * j + 2 * t) * 4) : "memory");
      P[j][0] = pack_bf16(fmaf(acc[4 * j], r0, mr0 * c0), fmaf(acc[4 * j + 1], r0, mr0 * c1));
      P[j][1] = pack_bf16(fmaf(acc[4 * j + 2], r1, mr1 * c0), fmaf(acc[4 * j + 3], r1, mr1 * c1));
    };
#pragma unroll
    for (int j = 8; j < 24; j++) fold(j);
#pragma unroll
    for (int j = 16; j < 24; j++) { P[j][0] = movm(P[j][0]); P[j][1] = movm(P[j][1]); }
    if (warp == 7) {
#pragma unroll
      for (int k = 0; k < 8; k++)
        asm volatile("st.relaxed.gpu.global.v2.b64 [%0], {%1, %2};" ::"l"(&g_s.halo[role][k][lane]),
                     "l"(((uint64_t)(ep + 1) << 32) | P[8 + 2 * k][1]), "l"(((uint64_t)(ep + 1) << 32) | P[9 + 2 * k][1]) : "memory");
    }
    bar_sync<8, 384>();
#pragma unroll
    for (int k = 0; k < 4; k++)
      sts128(sb + OFF_R0 + ((warp * 4 + k) * 32 + lane) * 16, P[8 + 4 * k][1], P[9 + 4 * k][1], P[10 + 4 * k][1], P[11 + 4 * k][1]);
#pragma unroll
    for (int j = 0; j < 8; j++) fold(j);
    if (tid == 0) PROF(27);
    bar_sync<5, 256>();
    const bool first = (warp == 0) && ((tb & 7) == 0);
    if (warp > 0) {
#pragma unroll
      for (int k = 0; k < 4; k++)
        lds128(sb + OFF_R0 + (((warp - 1) * 4 + k) * 32 + lane) * 16, H[4 * k], H[4 * k + 1], H[4 * k + 2], H[4 * k + 3]);
    } else {
      const int src = first ? role : role - 8;
      uint32_t bad;
      do {
        if (HALO_NS) __nanosleep(HALO_NS);
        bad = 0;
#pragma unroll
        for (int k = 0; k < 8; k++) {
          uint64_t a, b;
          asm volatile("ld.relaxed.gpu.global.v2.b64 {%0, %1}, [%2];" : "=l"(a), "=l"(b) : "l"(&g_s.halo[src][k][lane]) : "memory");
          H[2 * k] = (uint32_t)a;
          H[2 * k + 1] = (uint32_t)b;
          bad |= ((uint32_t)(a >> 32) ^ (ep + 1)) | ((uint32_t)(b >> 32) ^ (ep + 1));
        }
      } while (__any_sync(0xffffffffu, bad != 0));
    }
    __syncwarp();
    if (tid == 0) PROF(28);
    if (tid == 128) PROF(29);
    const uint32_t r8 = lane & 7, mi = lane >> 3;
    {
      const bool c0 = (2 * t <= g), c1 = (2 * t + 1 <= g);
      const uint32_t mcur = (c0 ? 0x0000ffffu : 0u) | (c1 ? 0xffff0000u : 0u);
      const uint32_t rowaddr = sb + OFF_R0 + (warp * 16 + (mi & 1) * 8 + r8) * 128;
      uint32_t LA[4], LB[4], Z[4], z, dep = 0;
      if (lane == 0) mbar_arrive(sb + BAR_RDY);
      bar_sync<13, 384>();
      lds128(sb + OFF_ZERO, Z[0], Z[1], Z[2], Z[3]);
#pragma unroll
      for (int h = 0; h < 4; h++) {
        float sp[4], s0[4], s1[4];
        mma16816z(sp, P[2 * h][0], P[2 * h][1], P[2 * h + 1][0], P[2 * h + 1][1], H[2 * h], H[2 * h + 1], Z);
        mma16816z(s0, P[2 * h][0], P[2 * h][1], P[2 * h + 1][0], P[2 * h + 1][1], P[8 + 2 * h][0], P[9 + 2 * h][0], Z);
        mma16816z(s1, P[2 * h][0], P[2 * h][1], P[2 * h + 1][0], P[2 * h + 1][1], P[8 + 2 * h][1], P[9 + 2 * h][1], Z);
        dep |= __float_as_uint(sp[0]) | __float_as_uint(s0[0]);
        dep |= __float_as_uint(s1[2]);
        if (first) { sp[0] = -1e9f; sp[1] = -1e9f; }
        LA[h] = pack_bf16(c0 ? s0[0] : sp[0], c0 ? s1[2] : s0[2]);
        LB[h] = pack_bf16(c1 ? s0[1] : sp[1], c1 ? s1[3] : s0[3]);
      }
      bar_arrive_after<14>(384, dep, Z[0]);
      asm volatile("ld.shared.u32 %0, [%1];" : "=r"(z) : "r"(sb + OFF_ZERO) : "memory");
      uint32_t A4[4][4], BC[4], Pa[4], Pb[4];
#pragma unroll
      for (int h = 0; h < 4; h++) {
        uint32_t mx = hmax2_bf(LA[h], LB[h]) | z;
        mx = hmax2_bf(mx, __shfl_xor_sync(0xffffffffu, mx, 1));
        mx = hmax2_bf(mx, __shfl_xor_sync(0xffffffffu, mx, 2));
        const float C = 0.25f * 1.4426950408889634f;
        const float na = -C * bf_lo(mx), nb = -C * bf_hi(mx);
        Pa[h] = pack_bf16(ex2(fmaf(bf_lo(LA[h]), C, na)), ex2(fmaf(bf_lo(LB[h]), C, na)));
        Pb[h] = pack_bf16(ex2(fmaf(bf_hi(LA[h]), C, nb)), ex2(fmaf(bf_hi(LB[h]), C, nb)));
        A4[h][0] = Pa[h] & ~mcur; A4[h][1] = z; A4[h][2] = Pa[h] & mcur; A4[h][3] = Pb[h] & ~mcur;
        BC[h] = Pb[h] & mcur;
      }
      if (lane == 0) mbar_arrive(sb + BAR_RDY + (((A4[0][0] | A4[1][0] | A4[2][0]) | (A4[3][0] | BC[0] | BC[1]) | (BC[2] | BC[3])) & z));
      bar_sync<13, 384>();
      lds128(sb + OFF_ZERO, Z[0], Z[1], Z[2], Z[3]);
      float O[4][8], SM[4][2];
#pragma unroll
      for (int h = 0; h < 4; h++) {
        float o0[4], o1[4], e0[4], e1[4], sm[4];
        mma16816z(o0, A4[h][0], A4[h][1], A4[h][2], A4[h][3], H[8 + 2 * h], P[16 + 2 * h][0], Z);
        mma16816z(o1, A4[h][0], A4[h][1], A4[h][2], A4[h][3], H[9 + 2 * h], P[17 + 2 * h][0], Z);
        mma1688z(e0, z, BC[h], P[16 + 2 * h][1], Z);
        mma1688z(e1, z, BC[h], P[17 + 2 * h][1], Z);
        mma1688z(sm, Pa[h], Pb[h], 0x3F803F80u, Z);
        dep |= __float_as_uint(o0[0]) | __float_as_uint(o1[0]);
        dep |= __float_as_uint(e0[2]) | __float_as_uint(e1[2]);
        dep |= __float_as_uint(sm[0]);
        O[h][0] = o0[0]; O[h][1] = o0[1]; O[h][2] = o0[2] + e0[2]; O[h][3] = o0[3] + e0[3];
        O[h][4] = o1[0]; O[h][5] = o1[1]; O[h][6] = o1[2] + e1[2]; O[h][7] = o1[3] + e1[3];
        SM[h][0] = sm[0]; SM[h][1] = sm[2];
      }
      bar_arrive_after<14>(384, dep, Z[0]);
      asm volatile("ld.shared.u32 %0, [%1];" : "=r"(z) : "r"(sb + OFF_ZERO) : "memory");
#pragma unroll
      for (int h = 0; h < 4; h++) {
        const float ia = rcp(SM[h][0] + __uint_as_float(z)), ib = rcp(SM[h][1] + __uint_as_float(z));
        stsm4(rowaddr + (((2 * h + (mi >> 1)) ^ r8) << 4), pack_bf16(O[h][0] * ia, O[h][1] * ia), pack_bf16(O[h][2] * ib, O[h][3] * ib),
              pack_bf16(O[h][4] * ia, O[h][5] * ia), pack_bf16(O[h][6] * ib, O[h][7] * ib));
      }
    }
    if (tid == 0) PROF(30);
    if (tid == 128) PROF(31);
    fence_async_smem();
    if (lane == 0) mbar_arrive(sb + BAR_RDY);
    bar_sync<13, 384>();
    if ((tid & 127) == 0) {
      tma3_st(&mp.m[M_O3], sb + OFF_R0 + wg * 8192, ta * 64, tb >> 3, (tb & 7) * 128 + wg * 64);
      bulk_commit();
      bulk_wait0();
      if (tid == 0) PROF(32);
      red_relaxed(ctr + 32 * (32 + (tb & 7)), 1);
      mbar_arrive(sb + BAR_OST);
      if (tid == 0) PROF(21);
    }
    __syncwarp();
    bar_arrive<14, 384>();
    if (wg == 0) {
      float ao[64];
      undef_regs(ao);
      bar_sync<3, 256>();
#pragma unroll 1
      for (n = N_OP; n < N_END; n++) {
        mbar_wait(full_bar(sb, n), (n >> 3) & 1);
        if (n == N_OP && tid == 0) PROF(22);
        const uint32_t a = dlo(slot_addr(sb, n));
        wg_fence();
#pragma unroll
        for (int kk = 0; kk < 4; kk++) wgmma_n128<1, 0>(ao, dsc(a + kk * 128), dsc(a + 512 + kk * 2), n != N_OP || kk != 0);
        wg_commit();
      }
      uint32_t G[32], X[32];
      mbar_wait(sb + BAR_X, 0);
      const uint32_t xaddr = sb + OFF_R1 + ((mi >> 1) * 8 + r8) * 128 + (((2 * warp + (mi & 1)) ^ r8) << 4);
#pragma unroll
      for (int k = 0; k < 8; k++) ldsm4t(xaddr + k * 2048, X[4 * k], X[4 * k + 1], X[4 * k + 2], X[4 * k + 3]);
      bar_sync<4, 256>();
#pragma unroll
      for (int k = 0; k < 8; k++) ldsm4t(xaddr - 16384 + k * 2048, G[4 * k], G[4 * k + 1], G[4 * k + 2], G[4 * k + 3]);
      wg_wait<0>();
      fence_regs(ao);
      if (tid == 0) { mbar_arrive(sb + BAR_DONE); PROF(23); }
#pragma unroll
      for (int hf = 0; hf < 2; hf++) {
#pragma unroll
        for (int k = 4 * hf; k < 4 * hf + 4; k++) {
          uint32_t o4[4];
#pragma unroll
          for (int q = 0; q < 4; q++)
            o4[q] = hadd2_bf(X[4 * k + q], hmul2_bf(pack_bf16(ao[8 * k + 2 * q], ao[8 * k + 2 * q + 1]), G[4 * k + q]));
          stsm4t(xaddr + k * 2048, o4[0], o4[1], o4[2], o4[3]);
        }
        if (FIN == 2 || hf == 1) {
          fence_async_smem();
          bar_sync<6, 128>();
          if (tid == 0) {
            if (FIN == 2) tma3_st(&mp.m[M_OUT], sb + OFF_R1 + hf * 8192, ta * 64, tb * 128 + hf * 64, 0);
            else { tma3_st(&mp.m[M_OUT], sb + OFF_R1, ta * 64, tb * 128, 0); tma3_st(&mp.m[M_OUT], sb + OFF_R1 + 8192, ta * 64, tb * 128 + 64, 0); }
            bulk_commit();
            if (hf == 1) asm volatile("cp.async.bulk.wait_group.read 0;" ::: "memory");
          }
        }
      }
      if (tid == 0) {
        if (role == 0) ctr[0] = ep + 1;
        PROF(24);
      }
    }
  }
}

typedef CUresult (*EncFn)(CUtensorMap*, CUtensorMapDataType, cuuint32_t, void*, const cuuint64_t*, const cuuint64_t*,
                          const cuuint32_t*, const cuuint32_t*, CUtensorMapInterleave, CUtensorMapSwizzle,
                          CUtensorMapL2promotion, CUtensorMapFloatOOBfill);

void enc(EncFn f, CUtensorMap* m, const void* p, cuuint64_t d0, cuuint64_t d1, cuuint64_t d2, cuuint64_t s1,
         cuuint64_t s2, cuuint32_t b0, cuuint32_t b1, cuuint32_t b2) {
  cuuint64_t gd[3] = {d0, d1, d2}, gs[2] = {s1, s2};
  cuuint32_t bd[3] = {b0, b1, b2}, es[3] = {1, 1, 1};
  f(m, CU_TENSOR_MAP_DATA_TYPE_BFLOAT16, 3, const_cast<void*>(p), gd, gs, bd, es, CU_TENSOR_MAP_INTERLEAVE_NONE,
    CU_TENSOR_MAP_SWIZZLE_128B, CU_TENSOR_MAP_L2_PROMOTION_L2_128B, CU_TENSOR_MAP_FLOAT_OOB_FILL_NONE);
}

}

extern "C" void kernel_launch(void* const* d_in, const int* in_sizes, int n_in, void* d_out, int out_size) {
  (void)in_sizes; (void)n_in; (void)out_size;
  const __nv_bfloat16* x = (const __nv_bfloat16*)d_in[0];
  const __nv_bfloat16* wqkv = (const __nv_bfloat16*)d_in[1];
  const __nv_bfloat16* wo = (const __nv_bfloat16*)d_in[2];
  const __nv_bfloat16* w1 = (const __nv_bfloat16*)d_in[4];
  const __nv_bfloat16* b1 = (const __nv_bfloat16*)d_in[5];
  const __nv_bfloat16* w2 = (const __nv_bfloat16*)d_in[6];
  const __nv_bfloat16* b2 = (const __nv_bfloat16*)d_in[7];

  void* fp = nullptr;
  cudaDriverEntryPointQueryResult qr;
  cudaGetDriverEntryPoint("cuTensorMapEncodeTiled", &fp, cudaEnableDefault, &qr);
  EncFn f = (EncFn)fp;
  Scratch* sc = nullptr;
  cudaGetSymbolAddress((void**)&sc, g_s);
  Maps mp;
  enc(f, &mp.m[M_X3], x, 512, 2, 1024, 1024, 2048, 64, 1, 128);
  enc(f, &mp.m[M_W3], wqkv, 512, 512, 3, 3072, 1024, 64, 64, 3);
  enc(f, &mp.m[M_H], sc->h, 512, 2048, 1, 1024, 1024 * 2048, 64, 64, 1);
  enc(f, &mp.m[M_W1], w1, 64, 2048, 28, 3584, 128, 64, 64, 2);
  enc(f, &mp.m[M_U], sc->u, 512, 1792, 1, 1024, 1024 * 1792, 64, 64, 1);
  enc(f, &mp.m[M_W2], w2, 64, 1792, 32, 4096, 128, 64, 64, 2);
  enc(f, &mp.m[M_WO], wo, 512, 512, 1, 1024, 1024 * 512, 64, 64, 1);
  enc(f, &mp.m[M_O2], sc->o, 512, 2048, 1, 1024, 1024 * 2048, 64, 128, 1);
  enc(f, &mp.m[M_O3], sc->o, 512, 2, 1024, 1024, 2048, 64, 1, 64);
  enc(f, &mp.m[M_X2], x, 512, 2048, 1, 1024, 1024 * 2048, 64, 128, 1);
  enc(f, &mp.m[M_OUT], d_out, 512, 2048, 1, 1024, 1024 * 2048, 64, 64, 1);
  for (int sm = 0; sm < 160; sm++) {
    int gpc, idx;
    if (sm < 64) { gpc = (sm >> 1) & 7; idx = (sm >> 4) * 2 + (sm & 1); }
    else if (sm < 120) { const int tp = (sm - 64) >> 1; gpc = 1 + tp % 7; idx = 8 + (tp / 7) * 2 + (sm & 1); }
    else { gpc = 0; idx = sm - 116; }
    const int a = (gpc & 1) * 4 + (idx & 3), b = (gpc >> 1) * 4 + (idx >> 2);
    mp.role[sm] = (sm >= 120 && sm < 124) || sm >= 132 ? 255 : (uint8_t)(b * 8 + a);
  }
  cudaFuncSetAttribute(fused_kernel, cudaFuncAttributeMaxDynamicSharedMemorySize, SMEM_BYTES);
  fused_kernel<<<132, 512, SMEM_BYTES, cudaStreamPerThread>>>(mp, x, wqkv, wo, w1, b1, w2, b2, (__nv_bfloat16*)d_out);
}
```

```cpp
#include <cuda_runtime.h>
#include <cuda.h>
#include <cuda_bf16.h>
#include <stdint.h>

namespace {

constexpr int S_ = 2048, D_ = 512, F_ = 1792;
constexpr uint64_t WATCHDOG_NS = 2000000000ull;
#define HOLD2 1
#define OWIN 1
#define HALO_NS 1800
#define XAT 1
#define QEARLY 0
#define NOPAUSE 1
#define CS_NS 300
#define UGRP 2
#define FOLDGAP 0
#define LNH 0
constexpr int KA = 8;
constexpr int NSLOT = 8;
constexpr int SLOT = 24576;
constexpr int OFF_R0 = NSLOT * SLOT;
constexpr int OFF_R1 = OFF_R0 + 16384;
constexpr int OFF_CS = OFF_R1 + 16384;
constexpr int OFF_BIAS = OFF_CS + 768;
constexpr int OFF_BAR = OFF_BIAS + 512;
constexpr int BAR_FULL = OFF_BAR, BAR_FLAG = BAR_FULL + 64, BAR_X = BAR_FLAG + 40, BAR_DONE = BAR_X + 8, BAR_LN = BAR_X + 16,
              BAR_EMPTY = BAR_FULL + 128, BAR_PUB = BAR_EMPTY + 64, BAR_OST = BAR_PUB + 8, OFF_ZERO = BAR_PUB + 16,
              BAR_BIAS = BAR_PUB + 32, OFF_EP = BAR_PUB + 40;
constexpr int SMEM_BYTES = OFF_BAR + 256;

struct __align__(1024) Scratch {
  uint32_t ctr[40 * 32];
  float2 stats[S_];
  float colsum[8][192];
  uint4 halo[128][8][32];
  __nv_bfloat16 h[S_ * D_];
  __nv_bfloat16 u[D_ * F_];
  __nv_bfloat16 o[S_ * D_];
};
__device__ Scratch g_s;

enum { M_W3, M_X3, M_W1, M_H, M_W2, M_U, M_WO, M_O2, M_O3, M_X2, M_OUT, NMAPS };
struct Maps {
  CUtensorMap m[NMAPS];
  uint8_t role[160];
};

__device__ __forceinline__ uint32_t smem_u32(const void* p) { return (uint32_t)__cvta_generic_to_shared(p); }
__device__ __forceinline__ void mbar_init(uint32_t bar, uint32_t cnt) {
  asm volatile("mbarrier.init.shared::cta.b64 [%0], %1;" ::"r"(bar), "r"(cnt) : "memory");
}
__device__ __forceinline__ void mbar_expect_tx(uint32_t bar, uint32_t bytes) {
  asm volatile("mbarrier.arrive.expect_tx.shared::cta.b64 _, [%0], %1;" ::"r"(bar), "r"(bytes) : "memory");
}
__device__ __forceinline__ void mbar_arrive(uint32_t bar) {
  asm volatile("mbarrier.arrive.shared::cta.b64 _, [%0];" ::"r"(bar) : "memory");
}
__device__ __forceinline__ void mbar_arrive_n(uint32_t bar, uint32_t n) {
  asm volatile("mbarrier.arrive.shared::cta.b64 _, [%0], %1;" ::"r"(bar), "r"(n) : "memory");
}
__device__ __forceinline__ void mbar_wait(uint32_t bar, uint32_t parity) {
  asm volatile("{\n.reg .pred p;\nLAB_WAIT:\nmbarrier.try_wait.parity.shared::cta.b64 p, [%0], %1;\n@!p bra LAB_WAIT;\n}" ::"r"(bar),
               "r"(parity)
               : "memory");
}
__device__ __forceinline__ uint32_t mbar_try(uint32_t bar, uint32_t parity) {
  uint32_t ok;
  asm volatile("{\n.reg .pred p;\nmbarrier.try_wait.parity.shared::cta.b64 p, [%1], %2;\nselp.b32 %0, 1, 0, p;\n}"
               : "=r"(ok) : "r"(bar), "r"(parity) : "memory");
  return ok;
}
__device__ __forceinline__ uint32_t mbar_test(uint32_t bar, uint32_t parity) {
  uint32_t ok;
  asm volatile("{\n.reg .pred p;\nmbarrier.test_wait.parity.shared::cta.b64 p, [%1], %2;\nselp.b32 %0, 1, 0, p;\n}"
               : "=r"(ok) : "r"(bar), "r"(parity) : "memory");
  return ok;
}
__device__ __forceinline__ bool elect_one() {
  uint32_t p;
  asm volatile("{\n.reg .pred P;\nelect.sync _|P, 0xffffffff;\nselp.b32 %0, 1, 0, P;\n}" : "=r"(p));
  return p;
}
__device__ __forceinline__ void tma3(uint32_t dst, const CUtensorMap* tm, uint32_t bar, int c0, int c1, int c2) {
  asm volatile(
      "cp.async.bulk.tensor.3d.shared::cluster.global.mbarrier::complete_tx::bytes [%0], [%1, {%3, %4, %5}], [%2];" ::"r"(dst),
      "l"(tm), "r"(bar), "r"(c0), "r"(c1), "r"(c2)
      : "memory");
}
__device__ __forceinline__ void tma3_st(const CUtensorMap* tm, uint32_t src, int c0, int c1, int c2) {
  asm volatile("cp.async.bulk.tensor.3d.global.shared::cta.bulk_group [%0, {%2, %3, %4}], [%1];" ::"l"(tm), "r"(src),
               "r"(c0), "r"(c1), "r"(c2)
               : "memory");
}
__device__ __forceinline__ void bulk_commit() { asm volatile("cp.async.bulk.commit_group;" ::: "memory"); }
__device__ __forceinline__ void bulk_wait0() { asm volatile("cp.async.bulk.wait_group 0;" ::: "memory"); }
__device__ __forceinline__ void bulk_wait0_read() { asm volatile("cp.async.bulk.wait_group.read 0;" ::: "memory"); }
__device__ __forceinline__ void prefetch_map(const CUtensorMap* tm) {
  asm volatile("prefetch.tensormap [%0];" ::"l"(tm) : "memory");
}
__device__ __forceinline__ void fence_async_smem() { asm volatile("fence.proxy.async.shared::cta;" ::: "memory"); }
__device__ __forceinline__ void fence_async_global() { asm volatile("fence.proxy.async.global;" ::: "memory"); }
__device__ __forceinline__ void wg_fence() { asm volatile("wgmma.fence.sync.aligned;" ::: "memory"); }
__device__ __forceinline__ void wg_commit() { asm volatile("wgmma.commit_group.sync.aligned;" ::: "memory"); }
template <int N>
__device__ __forceinline__ void wg_wait() { asm volatile("wgmma.wait_group.sync.aligned %0;" ::"n"(N) : "memory"); }
template <int N>
__device__ __forceinline__ void fence_regs(float (&d)[N]) {
#pragma unroll
  for (int i = 0; i < N; i++) asm volatile("" : "+f"(d[i])::"memory");
}
template <int N>
__device__ __forceinline__ void undef_regs(float (&d)[N]) {
#pragma unroll
  for (int i = 0; i < N; i++) asm volatile("" : "=f"(d[i]));
}
template <int ID, int N>
__device__ __forceinline__ void bar_sync() { asm volatile("bar.sync %0, %1;" ::"n"(ID), "n"(N) : "memory"); }
template <int ID>
__device__ __forceinline__ void bar_arrive_after(uint32_t n, uint32_t dep, uint32_t zero) {
  asm volatile("bar.arrive %0, %1;" ::"n"(ID), "r"(n + (dep & zero)) : "memory");
}
template <int ID>
__device__ __forceinline__ void bar_sync_after(uint32_t n, uint32_t dep, uint32_t zero) {
  asm volatile("bar.sync %0, %1;" ::"n"(ID), "r"(n + (dep & zero)) : "memory");
}
template <int ID, int N>
__device__ __forceinline__ void bar_arrive() { asm volatile("bar.arrive %0, %1;" ::"n"(ID), "n"(N) : "memory"); }
__device__ __forceinline__ uint32_t dlo(uint32_t addr) { return (addr >> 4) | (512u << 16); }
__device__ __forceinline__ uint64_t dsc(uint32_t lo) {
  uint64_t d;
  asm("mov.b64 %0, {%1, %2};" : "=l"(d) : "r"(lo), "r"(0x40000040u));
  return d;
}
__device__ __forceinline__ uint32_t ld_relaxed(const uint32_t* p) {
  uint32_t v;
  asm volatile("ld.relaxed.gpu.global.u32 %0, [%1];" : "=r"(v) : "l"(p) : "memory");
  return v;
}
__device__ __forceinline__ void red_release(uint32_t* p, uint32_t v) {
  asm volatile("red.release.gpu.global.add.u32 [%0], %1;" ::"l"(p), "r"(v) : "memory");
}
__device__ __forceinline__ uint32_t ld_acquire(const uint32_t* p) {
  uint32_t v;
  asm volatile("ld.acquire.gpu.global.u32 %0, [%1];" : "=r"(v) : "l"(p) : "memory");
  return v;
}
__device__ __forceinline__ void red_relaxed(uint32_t* p, uint32_t v) {
  asm volatile("red.relaxed.gpu.global.add.u32 [%0], %1;" ::"l"(p), "r"(v) : "memory");
}
__device__ __forceinline__ void bulk_st(void* dst, uint32_t src, uint32_t bytes) {
  asm volatile("cp.async.bulk.global.shared::cta.bulk_group [%0], [%1], %2;" ::"l"(dst), "r"(src), "r"(bytes) : "memory");
}
__device__ __forceinline__ void bulk_ld(uint32_t dst, const void* src, uint32_t bytes, uint32_t bar) {
  asm volatile("cp.async.bulk.shared::cluster.global.mbarrier::complete_tx::bytes [%0], [%1], %2, [%3];" ::"r"(dst), "l"(src),
               "r"(bytes), "r"(bar) : "memory");
}
__device__ __forceinline__ void wait_ctr(const uint32_t* p, uint32_t target) {
  while ((int32_t)(ld_acquire(p) - target) < 0) { }
}
__device__ __forceinline__ uint64_t globaltime() {
  uint64_t v;
  asm volatile("mov.u64 %0, %%globaltimer;" : "=l"(v));
  return v;
}
__device__ __forceinline__ uint32_t pack_bf16(float lo, float hi) {
  uint32_t r;
  asm("cvt.rn.bf16x2.f32 %0, %1, %2;" : "=r"(r) : "f"(hi), "f"(lo));
  return r;
}
__device__ __forceinline__ float bf_lo(uint32_t v) { return __uint_as_float(v << 16); }
__device__ __forceinline__ float bf_hi(uint32_t v) { return __uint_as_float(v & 0xffff0000u); }
__device__ __forceinline__ float bf_round(float x) { return bf_hi(pack_bf16(0.f, x)); }
__device__ __forceinline__ float ex2(float x) {
  float r;
  asm("ex2.approx.ftz.f32 %0, %1;" : "=f"(r) : "f"(x));
  return r;
}
__device__ __forceinline__ float rcp(float x) {
  float r;
  asm("rcp.approx.ftz.f32 %0, %1;" : "=f"(r) : "f"(x));
  return r;
}
__device__ __forceinline__ float tanh_fast(float x) {
  float r;
  asm("tanh.approx.f32 %0, %1;" : "=f"(r) : "f"(x));
  return r;
}
__device__ __forceinline__ uint32_t movm(uint32_t a) {
  uint32_t d;
  asm volatile("movmatrix.sync.aligned.m8n8.trans.b16 %0, %1;" : "=r"(d) : "r"(a));
  return d;
}
__device__ __forceinline__ void stsm4(uint32_t addr, uint32_t a, uint32_t b, uint32_t c, uint32_t d) {
  asm volatile("stmatrix.sync.aligned.m8n8.x4.shared.b16 [%0], {%1, %2, %3, %4};" ::"r"(addr), "r"(a), "r"(b), "r"(c), "r"(d)
               : "memory");
}
__device__ __forceinline__ void stsm4t(uint32_t addr, uint32_t a, uint32_t b, uint32_t c, uint32_t d) {
  asm volatile("stmatrix.sync.aligned.m8n8.x4.trans.shared.b16 [%0], {%1, %2, %3, %4};" ::"r"(addr), "r"(a), "r"(b), "r"(c),
               "r"(d)
               : "memory");
}
__device__ __forceinline__ void ldsm4t(uint32_t addr, uint32_t& a, uint32_t& b, uint32_t& c, uint32_t& d) {
  asm volatile("ldmatrix.sync.aligned.m8n8.x4.trans.shared.b16 {%0, %1, %2, %3}, [%4];"
               : "=r"(a), "=r"(b), "=r"(c), "=r"(d)
               : "r"(addr)
               : "memory");
}
__device__ __forceinline__ void sts128(uint32_t addr, uint32_t a, uint32_t b, uint32_t c, uint32_t d) {
  asm volatile("st.shared.v4.b32 [%0], {%1, %2, %3, %4};" ::"r"(addr), "r"(a), "r"(b), "r"(c), "r"(d) : "memory");
}
__device__ __forceinline__ void lds128(uint32_t addr, uint32_t& a, uint32_t& b, uint32_t& c, uint32_t& d) {
  asm volatile("ld.shared.v4.b32 {%0, %1, %2, %3}, [%4];" : "=r"(a), "=r"(b), "=r"(c), "=r"(d) : "r"(addr) : "memory");
}
__device__ __forceinline__ void mma16816(float (&c)[4], uint32_t a0, uint32_t a1, uint32_t a2, uint32_t a3, uint32_t b0,
                                         uint32_t b1) {
  asm volatile("mma.sync.aligned.m16n8k16.row.col.f32.bf16.bf16.f32 {%0,%1,%2,%3}, {%4,%5,%6,%7}, {%8,%9}, {%0,%1,%2,%3};"
               : "+f"(c[0]), "+f"(c[1]), "+f"(c[2]), "+f"(c[3])
               : "r"(a0), "r"(a1), "r"(a2), "r"(a3), "r"(b0), "r"(b1));
}
__device__ __forceinline__ void mma16816z(float (&c)[4], uint32_t a0, uint32_t a1, uint32_t a2, uint32_t a3, uint32_t b0,
                                          uint32_t b1, const uint32_t (&z)[4]) {
  asm volatile("mma.sync.aligned.m16n8k16.row.col.f32.bf16.bf16.f32 {%0,%1,%2,%3}, {%4,%5,%6,%7}, {%8,%9}, {%10,%11,%12,%13};"
               : "=f"(c[0]), "=f"(c[1]), "=f"(c[2]), "=f"(c[3])
               : "r"(a0), "r"(a1), "r"(a2), "r"(a3), "r"(b0), "r"(b1), "f"(__uint_as_float(z[0])), "f"(__uint_as_float(z[1])),
                 "f"(__uint_as_float(z[2])), "f"(__uint_as_float(z[3])));
}
__device__ __forceinline__ uint32_t hmax2_bf(uint32_t a, uint32_t b) {
  uint32_t r;
  asm("max.bf16x2 %0, %1, %2;" : "=r"(r) : "r"(a), "r"(b));
  return r;
}
__device__ __forceinline__ void mma1688z(float (&c)[4], uint32_t a0, uint32_t a1, uint32_t b0, const uint32_t (&z)[4]) {
  asm volatile("mma.sync.aligned.m16n8k8.row.col.f32.bf16.bf16.f32 {%0,%1,%2,%3}, {%4,%5}, {%6}, {%7,%8,%9,%10};"
               : "=f"(c[0]), "=f"(c[1]), "=f"(c[2]), "=f"(c[3])
               : "r"(a0), "r"(a1), "r"(b0), "f"(__uint_as_float(z[0])), "f"(__uint_as_float(z[1])), "f"(__uint_as_float(z[2])),
                 "f"(__uint_as_float(z[3])));
}
__device__ __forceinline__ void mma1688(float (&c)[4], uint32_t a0, uint32_t a1, uint32_t b0) {
  asm volatile("mma.sync.aligned.m16n8k8.row.col.f32.bf16.bf16.f32 {%0,%1,%2,%3}, {%4,%5}, {%6}, {%0,%1,%2,%3};"
               : "+f"(c[0]), "+f"(c[1]), "+f"(c[2]), "+f"(c[3])
               : "r"(a0), "r"(a1), "r"(b0));
}
__device__ __forceinline__ uint32_t hmul2_bf(uint32_t a, uint32_t b) {
  uint32_t r;
  asm("mul.rn.bf16x2 %0, %1, %2;" : "=r"(r) : "r"(a), "r"(b));
  return r;
}
__device__ __forceinline__ uint32_t hsub2_bf(uint32_t a, uint32_t b) {
  uint32_t r;
  asm("sub.rn.bf16x2 %0, %1, %2;" : "=r"(r) : "r"(a), "r"(b));
  return r;
}
__device__ __forceinline__ uint32_t hfma2_bf(uint32_t a, uint32_t b, uint32_t c) {
  uint32_t r;
  asm("fma.rn.bf16x2 %0, %1, %2, %3;" : "=r"(r) : "r"(a), "r"(b), "r"(c));
  return r;
}
__device__ __forceinline__ float sqrt_fast(float x) {
  float r;
  asm("sqrt.approx.ftz.f32 %0, %1;" : "=f"(r) : "f"(x));
  return r;
}
__device__ __forceinline__ uint32_t hadd2_bf(uint32_t a, uint32_t b) {
  uint32_t r;
  asm("add.rn.bf16x2 %0, %1, %2;" : "=r"(r) : "r"(a), "r"(b));
  return r;
}

template <int TA, int TB>
__device__ __forceinline__ void wgmma_n128(float (&d)[64], uint64_t da, uint64_t db, int sd) {
  asm volatile(
      "{\n.reg .pred p;\nsetp.ne.b32 p, %66, 0;\n"
      "wgmma.mma_async.sync.aligned.m64n128k16.f32.bf16.bf16 {"
      "%0, %1, %2, %3, %4, %5, %6, %7, %8, %9, %10, %11, %12, %13, %14, %15, %16, %17, %18, %19, %20, %21, %22, %23, "
      "%24, %25, %26, %27, %28, %29, %30, %31, %32, %33, %34, %35, %36, %37, %38, %39, %40, %41, %42, %43, %44, %45, "
      "%46, %47, %48, %49, %50, %51, %52, %53, %54, %55, %56, %57, %58, %59, %60, %61, %62, %63"
      "}, %64, %65, p, 1, 1, %67, %68;\n}\n"
      :
      "+f"(d[0]), "+f"(d[1]), "+f"(d[2]), "+f"(d[3]), "+f"(d[4]), "+f"(d[5]), "+f"(d[6]), "+f"(d[7]), "+f"(d[8]),
      "+f"(d[9]), "+f"(d[10]), "+f"(d[11]), "+f"(d[12]), "+f"(d[13]), "+f"(d[14]), "+f"(d[15]), "+f"(d[16]),
      "+f"(d[17]), "+f"(d[18]), "+f"(d[19]), "+f"(d[20]), "+f"(d[21]), "+f"(d[22]), "+f"(d[23]), "+f"(d[24]),
      "+f"(d[25]), "+f"(d[26]), "+f"(d[27]), "+f"(d[28]), "+f"(d[29]), "+f"(d[30]), "+f"(d[31]), "+f"(d[32]),
      "+f"(d[33]), "+f"(d[34]), "+f"(d[35]), "+f"(d[36]), "+f"(d[37]), "+f"(d[38]), "+f"(d[39]), "+f"(d[40]),
      "+f"(d[41]), "+f"(d[42]), "+f"(d[43]), "+f"(d[44]), "+f"(d[45]), "+f"(d[46]), "+f"(d[47]), "+f"(d[48]),
      "+f"(d[49]), "+f"(d[50]), "+f"(d[51]), "+f"(d[52]), "+f"(d[53]), "+f"(d[54]), "+f"(d[55]), "+f"(d[56]),
      "+f"(d[57]), "+f"(d[58]), "+f"(d[59]), "+f"(d[60]), "+f"(d[61]), "+f"(d[62]), "+f"(d[63])
      : "l"(da), "l"(db), "r"(sd), "n"(TA), "n"(TB));
}

template <int TA, int TB>
__device__ __forceinline__ void wgmma_n192(float (&d)[96], uint64_t da, uint64_t db, int sd) {
  asm volatile(
      "{\n.reg .pred p;\nsetp.ne.b32 p, %98, 0;\n"
      "wgmma.mma_async.sync.aligned.m64n192k16.f32.bf16.bf16 {"
      "%0, %1, %2, %3, %4, %5, %6, %7, %8, %9, %10, %11, %12, %13, %14, %15, %16, %17, %18, %19, %20, %21, %22, %23, "
      "%24, %25, %26, %27, %28, %29, %30, %31, %32, %33, %34, %35, %36, %37, %38, %39, %40, %41, %42, %43, %44, %45, "
      "%46, %47, %48, %49, %50, %51, %52, %53, %54, %55, %56, %57, %58, %59, %60, %61, %62, %63, %64, %65, %66, %67, "
      "%68, %69, %70, %71, %72, %73, %74, %75, %76, %77, %78, %79, %80, %81, %82, %83, %84, %85, %86, %87, %88, %89, "
      "%90, %91, %92, %93, %94, %95"
      "}, %96, %97, p, 1, 1, %99, %100;\n}\n"
      :
      "+f"(d[0]), "+f"(d[1]), "+f"(d[2]), "+f"(d[3]), "+f"(d[4]), "+f"(d[5]), "+f"(d[6]), "+f"(d[7]), "+f"(d[8]),
      "+f"(d[9]), "+f"(d[10]), "+f"(d[11]), "+f"(d[12]), "+f"(d[13]), "+f"(d[14]), "+f"(d[15]), "+f"(d[16]),
      "+f"(d[17]), "+f"(d[18]), "+f"(d[19]), "+f"(d[20]), "+f"(d[21]), "+f"(d[22]), "+f"(d[23]), "+f"(d[24]),
      "+f"(d[25]), "+f"(d[26]), "+f"(d[27]), "+f"(d[28]), "+f"(d[29]), "+f"(d[30]), "+f"(d[31]), "+f"(d[32]),
      "+f"(d[33]), "+f"(d[34]), "+f"(d[35]), "+f"(d[36]), "+f"(d[37]), "+f"(d[38]), "+f"(d[39]), "+f"(d[40]),
      "+f"(d[41]), "+f"(d[42]), "+f"(d[43]), "+f"(d[44]), "+f"(d[45]), "+f"(d[46]), "+f"(d[47]), "+f"(d[48]),
      "+f"(d[49]), "+f"(d[50]), "+f"(d[51]), "+f"(d[52]), "+f"(d[53]), "+f"(d[54]), "+f"(d[55]), "+f"(d[56]),
      "+f"(d[57]), "+f"(d[58]), "+f"(d[59]), "+f"(d[60]), "+f"(d[61]), "+f"(d[62]), "+f"(d[63]), "+f"(d[64]),
      "+f"(d[65]), "+f"(d[66]), "+f"(d[67]), "+f"(d[68]), "+f"(d[69]), "+f"(d[70]), "+f"(d[71]), "+f"(d[72]),
      "+f"(d[73]), "+f"(d[74]), "+f"(d[75]), "+f"(d[76]), "+f"(d[77]), "+f"(d[78]), "+f"(d[79]), "+f"(d[80]),
      "+f"(d[81]), "+f"(d[82]), "+f"(d[83]), "+f"(d[84]), "+f"(d[85]), "+f"(d[86]), "+f"(d[87]), "+f"(d[88]),
      "+f"(d[89]), "+f"(d[90]), "+f"(d[91]), "+f"(d[92]), "+f"(d[93]), "+f"(d[94]), "+f"(d[95])
      : "l"(da), "l"(db), "r"(sd), "n"(TA), "n"(TB));
}

#define PROFV(i, v) do { } while (0)
#define WAITT(acc, stmt) do { stmt; } while (0)
#define PROF(i) do { } while (0)

constexpr uint32_t N_G1 = 2 * KA, N_QB = 2 * KA + 32, N_G2 = 48, N_OP = 76, N_END = 84;

__device__ __forceinline__ uint32_t full_bar(uint32_t sb, uint32_t n) { return sb + BAR_FULL + 8 * (n & 7); }
__device__ __forceinline__ uint32_t empty_bar(uint32_t sb, uint32_t n) { return sb + BAR_EMPTY + 8 * (n & 7); }
__device__ __forceinline__ uint32_t slot_addr(uint32_t sb, uint32_t n) { return sb + (n & 7) * SLOT; }

__global__ void __launch_bounds__(512, 1)
fused_kernel(const __grid_constant__ Maps mp, const __nv_bfloat16* __restrict__ x, const __nv_bfloat16* __restrict__ wqkv,
             const __nv_bfloat16* __restrict__ b1, const __nv_bfloat16* __restrict__ b2) {
  extern __shared__ __align__(1024) uint8_t smem_raw[];
  constexpr uint32_t sb = 1024;
  const int lane = threadIdx.x & 31;
  const int pwarp = __shfl_sync(0xffffffffu, threadIdx.x >> 5, 0);
  if (pwarp >= 14) prefetch_map(&mp.m[pwarp - 14]);

  uint32_t smid, nsm;
  asm volatile("mov.u32 %0, %%smid;" : "=r"(smid));
  asm volatile("mov.u32 %0, %%nsmid;" : "=r"(nsm));
  if (nsm != 132) smid = blockIdx.x;
  const uint32_t role = mp.role[smid];
  const int ta = role & 7;
  const int tb = role >> 3;
  const bool g1_active = tb < 14;
  uint32_t* const ctr = g_s.ctr;

  if (pwarp >= 14 && role < 252 && elect_one()) {
    const int q = pwarp - 14;
#pragma unroll
    for (int s = 0; s < 4; s++) mbar_init(sb + BAR_FULL + 8 * q + 16 * s, 1);
    if (q) mbar_init(sb + BAR_LN, 1);
    asm volatile("fence.mbarrier_init.release.cluster;" ::: "memory");
    if (q) {
      mbar_expect_tx(sb + BAR_LN, 16384);
      bulk_ld(sb + OFF_R1, x + role * 16 * D_, 16384, sb + BAR_LN);
    }
    mbar_expect_tx(full_bar(sb, q), q ? 16384 : 24576);
    tma3(slot_addr(sb, q), &mp.m[q], full_bar(sb, q), q ? 0 : ta * 64, q ? tb >> 3 : 0, q ? (tb & 7) * 128 : 0);
  }
  const int warp = pwarp < 4 ? pwarp + 8 : pwarp < 12 ? pwarp - 4 : pwarp;
  const int tid = warp * 32 + lane;
  const int g = lane >> 2, t = lane & 3;

  if (role >= 252) {
    uint32_t ep = 0;
    if (threadIdx.x == 0) {
      ep = ld_relaxed(ctr);
      red_relaxed(ctr + 32, 1 + (ep & (nsm >> 16)));
    }
    if (CS_NS) __nanosleep(CS_NS);
    const int grp = (role - 252) * 2 + (pwarp >> 3);
    float a[8] = {0.f, 0.f, 0.f, 0.f, 0.f, 0.f, 0.f, 0.f};
    if (lane < 24) {
      const uint4* pw = (const uint4*)(wqkv + (size_t)((pwarp & 7) * 64) * (3 * D_) + (lane >> 3) * D_ + grp * 64) + (lane & 7);
#pragma unroll 16
      for (int r = 0; r < 64; r++) {
        const uint4 q = __ldg(pw + r * (3 * D_ / 8));
        a[0] += bf_lo(q.x); a[1] += bf_hi(q.x); a[2] += bf_lo(q.y); a[3] += bf_hi(q.y);
        a[4] += bf_lo(q.z); a[5] += bf_hi(q.z); a[6] += bf_lo(q.w); a[7] += bf_hi(q.w);
      }
      const uint32_t dst = sb + pwarp * 768 + lane * 32;
      sts128(dst, __float_as_uint(a[0]), __float_as_uint(a[1]), __float_as_uint(a[2]), __float_as_uint(a[3]));
      sts128(dst + 16, __float_as_uint(a[4]), __float_as_uint(a[5]), __float_as_uint(a[6]), __float_as_uint(a[7]));
    }
    __syncthreads();
    if (threadIdx.x < 384) {
      const int gg = threadIdx.x >= 192, c = threadIdx.x - gg * 192;
      float sum = 0.f;
#pragma unroll
      for (int k = 0; k < 8; k++) {
        float v;
        asm volatile("ld.shared.f32 %0, [%1];" : "=f"(v) : "r"(sb + (gg * 8 + k) * 768 + c * 4) : "memory");
        sum += v;
      }
      asm volatile("st.shared.f32 [%0], %1;" ::"r"(sb + 16384 + threadIdx.x * 4), "f"(sum) : "memory");
      fence_async_smem();
    }
    __syncthreads();
    if (threadIdx.x == 0) {
      bulk_st(&g_s.colsum[(role - 252) * 2][0], sb + 16384, 1536);
      bulk_commit();
      bulk_wait0();
      red_relaxed(ctr + 32 * (8 + (role - 252) * 2), 1);
      red_relaxed(ctr + 32 * (9 + (role - 252) * 2), 1);
      for (int n = 0; (int32_t)(ld_acquire(ctr + 32) - (ep + 1) * 132) < 0; n++) {
        __nanosleep(200);
        if (n > (1 << 22)) __trap();
      }
    }
    return;
  }

  if (warp >= 12) {
    uint32_t ep = 0;
    if (warp == 14) ep = ld_relaxed(ctr);
    if (warp < 14 && elect_one()) {
      if (warp == 12) {
#pragma unroll
        for (int s = 0; s < 7; s++) mbar_init(sb + BAR_FLAG + 8 * s, 1);
      } else {
#pragma unroll
        for (int s = 0; s < 8; s++) mbar_init(sb + BAR_EMPTY + 8 * s, 8);
        mbar_init(sb + BAR_PUB, 4);
        mbar_init(sb + BAR_OST, 2);
        mbar_init(sb + BAR_BIAS, 1);
        sts128(sb + OFF_ZERO, 0, 0, 0, 0);
      }
      asm volatile("fence.mbarrier_init.release.cluster;" ::: "memory");
    }
    bar_sync<10, 128>();
    bar_arrive<0, 512>();
    asm volatile("setmaxnreg.dec.sync.aligned.u32 40;");
    if (warp < 14) {
      const int q = warp - 12;
      uint32_t n = 2 + q;
      if (LNH) mbar_wait(sb + BAR_LN, 0);
      const uint32_t own = g1_active ? 2 : 0, skip = own ? tb : 99, n_u2 = N_G2 + 14 + own / 2;
#pragma unroll 1
      for (int phase = 0; phase < 6; phase++) {
        uint32_t nend = (uint32_t)(((uint64_t)N_END << 40 | (uint64_t)N_OP << 32 | N_G2 << 16 | N_QB << 8 | N_G1) >> (8 * phase)) & 0xff;
        uint32_t base = (uint32_t)(((uint64_t)N_OP << 40 | (N_QB - 2 * KA) << 16 | N_G1 << 8) >> (8 * phase)) & 0xff;
        if (phase == 3) { nend = n_u2; base = N_G2 + own; }
        if (phase == 4) base = n_u2;
        auto kc = [&](uint32_t m) -> int {
          int tt = m - base;
          if (phase == 0 || phase == 2) tt >>= 1;
          if (phase == 3 || phase == 4) tt = tt < 0 ? 2 * tb + 2 + tt : 2 * (tt + (tt >= (int)skip)) + phase - 3;
          return tt * 64;
        };
        int mw = M_W2, w0 = 0, w2c = tb * 2;
        uint32_t bytes = 24576, offw = 8192, flag = sb + BAR_FLAG + 8 * (phase - 1);
        if (phase == 1) { mw = M_W1; flag = sb + BAR_FLAG; if (!g1_active) n += 32; }
        if (phase == 5) { mw = M_WO; w0 = ta * 64; w2c = 0; offw = 0; }
        if (phase == 0 || phase == 2) {
          mw = M_W3 + q; w0 = ta * 64; w2c = 0; offw = 0; flag = 0;
          if (q) bytes = 16384;
        }
        const CUtensorMap* tm = &mp.m[mw];
        uint32_t na = flag ? n + (phase == 3 ? own : 0) : 1000;
        bool go = !flag;
        int wk = kc(n), ak = kc(na);
#pragma unroll 1
        while (n < nend || na < nend) {
          if (n < nend && (go || mbar_test(empty_bar(sb, n), ((n >> 3) & 1) ^ 1))) {
            mbar_wait(empty_bar(sb, n), ((n >> 3) & 1) ^ 1);
            if (elect_one()) {
              mbar_expect_tx(full_bar(sb, n), n < base ? 16384 : bytes);
              const bool xt = mw == M_X3;
              tma3(slot_addr(sb, n) + offw, tm, full_bar(sb, n), xt ? wk : w0, xt ? tb >> 3 : wk, xt ? (tb & 7) * 128 : w2c);
            }
            __syncwarp();
            n += 2;
            wk = kc(n);
          }
          if (!go) {
            go = mbar_test(flag, 0);
            if (go && phase == 3 && q == 0 && lane == 0) { PROF(36); PROFV(38, n); }
            if (go) fence_async_global(); else __nanosleep(30);
          }
          if (go) {
#pragma unroll 1
            for (; na < n && na < nend; na += 2) {
              if (elect_one())
                tma3(slot_addr(sb, na) + (8192 - offw), tm + 1, full_bar(sb, na), phase == 5 ? ak : ta * 64, phase == 5 ? tb * 128 : ak, 0);
              __syncwarp();
              ak = kc(na + 2);
              if (na == base && phase == 3 && lane == 0) PROF(37);
            }
          }
        }
      }
    } else if (lane == 0) {
      if (warp == 14) {
        asm volatile("st.shared.u32 [%0], %1;" ::"r"(sb + OFF_EP), "r"(ep) : "memory");
#pragma unroll 1
        for (int i = M_W1; i < NMAPS; i++) prefetch_map(&mp.m[i]);
        mbar_wait(sb + BAR_PUB, 0);
        red_relaxed(ctr + 32, 1);
        PROF(5);
#pragma unroll 1
        for (int i = 0; i < 5; i++) {
          wait_ctr(ctr + 32 * (i ? 8 * i + (i == 4 ? tb >> 1 : i == 1 ? ta : ta >> UGRP) : 1),
                   (ep + 1) * ((uint32_t)((0x2000000184ull | (0x0E0E0000ull << UGRP)) >> (8 * i)) & 0xff));
          mbar_arrive(sb + BAR_FLAG + 8 * i);
          PROF(i == 0 ? 1 : i == 1 ? 42 : i == 2 ? 2 : i == 3 ? 43 : 3);
        }
      } else {
        if (smem_u32(smem_raw) != sb) __trap();
        mbar_expect_tx(sb + BAR_BIAS, 512);
        bulk_ld(sb + OFF_BIAS, b1 + (g1_active ? tb * 128 : 0), 256, sb + BAR_BIAS);
        bulk_ld(sb + OFF_BIAS + 256, b2 + tb * 128, 256, sb + BAR_BIAS);
        const uint64_t t0 = globaltime();
        while (!mbar_try(sb + BAR_DONE, 0))
          if (globaltime() - t0 > WATCHDOG_NS) __trap();
      }
    }
  } else if (warp >= 8) {
    const int w = warp - 8, t128 = tid - 256;
    {
      uint32_t v[32];
      const int lr = w * 4 + (g & 3);
      const uint32_t eo = lr * D_ + (g >> 2) * 256 + t * 8;
      bar_sync<0, 512>();
      mbar_wait(sb + BAR_LN, 0);
      if (t128 == 0) PROF(40);
#pragma unroll
      for (int i = 0; i < 8; i++) lds128(sb + OFF_R1 + (eo + i * 32) * 2, v[4 * i], v[4 * i + 1], v[4 * i + 2], v[4 * i + 3]);
      float sa[2] = {0.f, 0.f}, qa[2] = {0.f, 0.f};
#pragma unroll
      for (int k = 0; k < 32; k++) {
        const float lo = bf_lo(v[k]), hi = bf_hi(v[k]);
        sa[0] += lo; sa[1] += hi;
        qa[0] = fmaf(lo, lo, qa[0]); qa[1] = fmaf(hi, hi, qa[1]);
      }
      float sum = sa[0] + sa[1], sq = qa[0] + qa[1];
#pragma unroll
      for (int o = 1; o < 4; o <<= 1) {
        sum += __shfl_xor_sync(0xffffffffu, sum, o);
        sq += __shfl_xor_sync(0xffffffffu, sq, o);
      }
      sum += __shfl_xor_sync(0xffffffffu, sum, 16);
      sq += __shfl_xor_sync(0xffffffffu, sq, 16);
      if (t128 == 0) PROF(4);
      const float m = sum * (1.f / D_);
      const float var = fmaxf(fmaf(-m, m, sq * (1.f / D_)), 0.f);
      const uint32_t mb2 = pack_bf16(m, m);
      const float inv = rcp(bf_round(sqrt_fast(bf_round(bf_round(var) + 1e-5f))));
      const float inv2 = rcp(bf_round(sqrt_fast(bf_round(bf_round(var * inv * inv) + 1e-5f))));
      const float sc = inv * inv2, sh = (bf_lo(mb2) - m) * sc;
      const uint32_t sh2 = pack_bf16(sh, sh), sch = pack_bf16(sc, sc);
      const float scl = sc - bf_lo(sch);
      const uint32_t scl2 = pack_bf16(scl, scl);
      if (lane < 16 && t == 0)
        asm volatile("st.shared.v2.f32 [%0], {%1, %2};" ::"r"(sb + OFF_R0 + lr * 8), "f"(bf_lo(mb2)), "f"(inv) : "memory");
#pragma unroll
      for (int i = 0; i < 8; i++) {
        uint32_t o[4];
#pragma unroll
        for (int k = 0; k < 4; k++) {
          const uint32_t cc = hsub2_bf(v[4 * i + k], mb2);
          o[k] = hfma2_bf(cc, sch, hfma2_bf(cc, scl2, sh2));
        }
        sts128(sb + OFF_R1 + (eo + i * 32) * 2, o[0], o[1], o[2], o[3]);
      }
      if (t128 == 0) PROF(25);
      fence_async_smem();
      if (LNH) bar_arrive<9, 384>();
      __syncwarp();
      if (lane == 0) {
        if (w == 0) PROF(26);
        bulk_st(g_s.h + (size_t)(role * 16 + w * 4) * D_, sb + OFF_R1 + w * 4096, 4096);
        bulk_st(g_s.stats + role * 16 + w * 4, sb + OFF_R0 + w * 32, 32);
        bulk_commit();
      }
      if (lane == 0) {
        bulk_wait0();
        mbar_arrive(sb + BAR_PUB);
      }
      bar_sync<1, 128>();
    }
    const uint32_t taddr = sb + OFF_R0 + ((lane >> 4) * 8 + (lane & 7)) * 128 + (((2 * w + ((lane >> 3) & 1)) ^ (lane & 7)) << 4);
    if (!g1_active) { bar_sync<11, 384>(); bar_arrive<2, 384>(); }
#pragma unroll 1
    for (int ph = g1_active ? 0 : 1; ph < 2; ph++) {
      float acc[64];
      undef_regs(acc);
      long long wsum = 0;
      (void)wsum;
      const uint32_t n0 = ph ? N_G2 : N_G1, n1 = ph ? N_OP : N_QB;
      if (ph) bar_sync<13, 384>(); else bar_sync<11, 384>();
      const uint32_t nown = g1_active ? 2 : 0;
      uint32_t ev = ph ? (1u << 27 | (OWIN >= 0 ? 1u << (OWIN & 31) : 0)) : 1u << 31;
      mbar_wait(full_bar(sb, n0), (n0 >> 3) & 1);
      if (t128 == 0) PROF(6 + 4 * ph);
#pragma unroll 1
      for (uint32_t n = n0;; n++) {
        const uint32_t b = dlo(slot_addr(sb, n)) + 512;
        const uint32_t a = n - N_G2 < nown ? dlo(sb + OFF_R0) + (n - N_G2) * 512 : b - 512;
        wg_fence();
        wgmma_n128<1, 1>(acc, dsc(a), dsc(b), n != n0);
        const uint32_t ready = mbar_test(full_bar(sb, n + 1), ((n + 1) >> 3) & 1), quiet = ~ev & 1;
        ev >>= 1;
        wgmma_n128<1, 1>(acc, dsc(a + 128), dsc(b + 128), 1);
        wg_commit();
        wg_wait<1>();
        if (n != n0 && lane == 0) mbar_arrive_n(empty_bar(sb, n - 1), 2);
        wgmma_n128<1, 1>(acc, dsc(a + 256), dsc(b + 256), 1);
        wgmma_n128<1, 1>(acc, dsc(a + 384), dsc(b + 384), 1);
        wg_commit();
        if (ready & quiet) continue;
        if (!quiet) {
          if (n == n1 - 1) break;
          bar_arrive<8, 384>();
          if (!NOPAUSE) bar_sync<14, 384>();
        }
        if (!ready) WAITT(wsum, mbar_wait(full_bar(sb, n + 1), ((n + 1) >> 3) & 1));
      }
      if (ph) bar_arrive<3, 256>(); else if (!HOLD2) bar_arrive<2, 384>();
      wg_wait<0>();
      fence_regs(acc);
      if (lane == 0) mbar_arrive_n(empty_bar(sb, n1 - 1), 2);
      if (t128 == 0) { PROF(7 + 4 * ph); PROFV(34 + ph, wsum); }
      uint32_t bh[16];
      mbar_wait(sb + BAR_BIAS, 0);
#pragma unroll
      for (int j = 0; j < 16; j++)
        asm volatile("ld.shared.u32 %0, [%1];" : "=r"(bh[j]) : "r"(sb + OFF_BIAS + ph * 256 + j * 16 + t * 4) : "memory");
      const float ca = ph ? 1.f : 2.f * 0.7978845608028654f, cb = ph ? 0.f : 8.f * 0.7978845608028654f * 0.044715f;
#pragma unroll
      for (int hf = 0; hf < 2; hf++) {
#pragma unroll
        for (int k = 0; k < 4; k++) {
          uint32_t R[4];
#pragma unroll
          for (int i = 0; i < 4; i++) {
            const uint32_t bv = hmul2_bf(bh[8 * hf + 2 * k + (i >> 1)], 0x3F003F00u);
            const int ai = 32 * hf + 8 * k + 2 * i;
            const float h0 = fmaf(acc[ai], 0.5f, bf_lo(bv)), h1 = fmaf(acc[ai + 1], 0.5f, bf_hi(bv));
            const float t0 = tanh_fast(h0 * fmaf(cb, h0 * h0, ca)), t1 = tanh_fast(h1 * fmaf(cb, h1 * h1, ca));
            R[i] = pack_bf16(fmaf(h0, t0, h0), fmaf(h1, t1, h1));
          }
          stsm4t(taddr + hf * 8192 + k * 2048, R[0], R[1], R[2], R[3]);
        }
        if (ph == 0) {
          fence_async_smem();
          if (HOLD2 && hf == 0) bar_arrive<2, 384>();
          bar_sync<1, 128>();
          if (t128 == 0) {
            if (hf == 0) PROF(8);
            tma3_st(&mp.m[M_U], sb + OFF_R0 + hf * 8192, ta * 64, tb * 128 + hf * 64, 0);
            bulk_commit();
            bulk_wait0();
            red_relaxed(ctr + 32 * (16 + 8 * hf + (ta >> UGRP)), 1);
            PROF(hf ? 33 : 9);
          }
          __syncwarp();
        }
      }
      if (ph) {
        bar_arrive<4, 256>();
        if (t128 == 0) PROF(12);
      }
    }
  } else {
    bar_sync<0, 512>();
    asm volatile("setmaxnreg.inc.sync.aligned.u32 168;");
    const int wg = warp >> 2;
    float acc[96];
    undef_regs(acc);
    uint32_t n = 0, ep = 0;
    float r0 = 0.f, r1 = 0.f, mr0 = 0.f, mr1 = 0.f;
    uint32_t ready = 0;
    if (LNH) bar_sync<9, 384>();
#pragma unroll 1
    for (int kb = 0; kb < 8; kb++) {
      if (!ready) {
        mbar_wait(full_bar(sb, n), (n >> 3) & 1);
        mbar_wait(full_bar(sb, n + 1), (n >> 3) & 1);
      }
      if (kb == 0 && tid == 0) PROF(16);
      const bool last = kb == KA - 1 || kb == 7;
      const uint32_t a = dlo(slot_addr(sb, n + 1) + wg * 8192), b = dlo(slot_addr(sb, n));
      wg_fence();
      wgmma_n192<0, 1>(acc, dsc(a), dsc(b), kb != 0);
      ready = (uint32_t)!last & mbar_test(full_bar(sb, n + 2), ((n + 2) >> 3) & 1) & mbar_test(full_bar(sb, n + 3), ((n + 2) >> 3) & 1);
      wgmma_n192<0, 1>(acc, dsc(a + 2), dsc(b + 128), 1);
      wg_commit();
      wg_wait<1>();
      if (kb != 0 && kb != KA && lane == 0) { mbar_arrive(empty_bar(sb, n - 2)); mbar_arrive(empty_bar(sb, n - 1)); }
      wgmma_n192<0, 1>(acc, dsc(a + 4), dsc(b + 256), 1);
      wgmma_n192<0, 1>(acc, dsc(a + 6), dsc(b + 384), 1);
      wg_commit();
      if (last) {
        bar_arrive<11, 384>();
        wg_wait<0>();
        if (lane == 0) { mbar_arrive(empty_bar(sb, n)); mbar_arrive(empty_bar(sb, n + 1)); }
      }
      n += 2;
    }
    wg_wait<0>();
    fence_regs(acc);
    if (tid == 0) PROF(17);
    {
      mbar_wait(sb + BAR_FLAG + 8, 0);
      asm volatile("ld.shared.u32 %0, [%1];" : "=r"(ep) : "r"(sb + OFF_EP) : "memory");
      const int i0 = (tb & 7) * 128 + warp * 16 + g;
      const float2 s0 = __ldcg(&g_s.stats[2 * i0 + (tb >> 3)]), s1 = __ldcg(&g_s.stats[2 * (i0 + 8) + (tb >> 3)]);
      r0 = s0.y; r1 = s1.y;
      if (tid < 192) asm volatile("st.shared.f32 [%0], %1;" ::"r"(sb + OFF_CS + tid * 4), "f"(__ldcg(&g_s.colsum[ta][tid])) : "memory");
      mr0 = -s0.x * r0; mr1 = -s1.x * r1;
      if (FOLDGAP) bar_sync<2, 384>(); else bar_sync<5, 256>();
    }

    uint32_t P[24][2], H[16];
    auto fold = [&](int j) {
      float c0, c1;
      asm volatile("ld.shared.v2.f32 {%0, %1}, [%2];" : "=f"(c0), "=f"(c1) : "r"(sb + OFF_CS + (8 * j + 2 * t) * 4) : "memory");
      P[j][0] = pack_bf16(fmaf(acc[4 * j], r0, mr0 * c0), fmaf(acc[4 * j + 1], r0, mr0 * c1));
      P[j][1] = pack_bf16(fmaf(acc[4 * j + 2], r1, mr1 * c0), fmaf(acc[4 * j + 3], r1, mr1 * c1));
    };
#pragma unroll
    for (int j = QEARLY ? 0 : 8; j < 24; j++) fold(j);
#pragma unroll
    for (int j = 16; j < 24; j++) { P[j][0] = movm(P[j][0]); P[j][1] = movm(P[j][1]); }
    if (warp == 7) {
#pragma unroll
      for (int k = 0; k < 8; k++)
        asm volatile("st.relaxed.gpu.global.v2.b64 [%0], {%1, %2};" ::"l"(&g_s.halo[role][k][lane]),
                     "l"(((uint64_t)(ep + 1) << 32) | P[8 + 2 * k][1]), "l"(((uint64_t)(ep + 1) << 32) | P[9 + 2 * k][1]) : "memory");
    }
    if (tid == 0) PROF(27);
    const bool first = (warp == 0) && ((tb & 7) == 0);
#pragma unroll
    for (int k = 0; k < 4; k++)
      sts128(sb + OFF_R1 + ((warp * 4 + k) * 32 + lane) * 16, P[8 + 4 * k][1], P[9 + 4 * k][1], P[10 + 4 * k][1], P[11 + 4 * k][1]);
    bar_sync<5, 256>();
    if (warp > 0) {
#pragma unroll
      for (int k = 0; k < 4; k++)
        lds128(sb + OFF_R1 + (((warp - 1) * 4 + k) * 32 + lane) * 16, H[4 * k], H[4 * k + 1], H[4 * k + 2], H[4 * k + 3]);
    } else {
      if (FOLDGAP && !g1_active) mbar_wait(sb + BAR_FLAG + 16, 0);
      const int src = first ? role : role - 8;
      uint32_t bad;
      do {
        if (HALO_NS) __nanosleep(HALO_NS);
        bad = 0;
#pragma unroll
        for (int k = 0; k < 8; k++) {
          uint64_t a, b;
          asm volatile("ld.relaxed.gpu.global.v2.b64 {%0, %1}, [%2];" : "=l"(a), "=l"(b) : "l"(&g_s.halo[src][k][lane]) : "memory");
          H[2 * k] = (uint32_t)a;
          H[2 * k + 1] = (uint32_t)b;
          bad |= ((uint32_t)(a >> 32) ^ (ep + 1)) | ((uint32_t)(b >> 32) ^ (ep + 1));
        }
      } while (__any_sync(0xffffffffu, bad != 0));
    }
    __syncwarp();
    if (tid == 0) PROF(28);
    if (tid == 128) PROF(29);
    const uint32_t r8 = lane & 7, mi = lane >> 3;
    {
      const bool c0 = (2 * t <= g), c1 = (2 * t + 1 <= g);
      const uint32_t mcur = (c0 ? 0x0000ffffu : 0u) | (c1 ? 0xffff0000u : 0u);
      const uint32_t rowaddr = sb + OFF_R1 + (warp * 16 + (mi & 1) * 8 + r8) * 128;
      uint32_t Z[4], dep = 0;
      if (FOLDGAP) bar_sync<5, 256>(); else bar_sync<2, 384>();
      lds128(sb + OFF_ZERO, Z[0], Z[1], Z[2], Z[3]);
      if (tid == 0) PROF(19);
#pragma unroll
      for (int j = 0; j < (QEARLY ? 0 : 8); j++) fold(j);
#pragma unroll
      for (int h = 0; h < 4; h++) {
        float sp[4], s0[4], s1[4];
        mma16816z(sp, P[2 * h][0], P[2 * h][1], P[2 * h + 1][0], P[2 * h + 1][1], H[2 * h], H[2 * h + 1], Z);
        mma16816z(s0, P[2 * h][0], P[2 * h][1], P[2 * h + 1][0], P[2 * h + 1][1], P[8 + 2 * h][0], P[9 + 2 * h][0], Z);
        mma16816z(s1, P[2 * h][0], P[2 * h][1], P[2 * h + 1][0], P[2 * h + 1][1], P[8 + 2 * h][1], P[9 + 2 * h][1], Z);
        if (first) { sp[0] = -1e9f; sp[1] = -1e9f; }
        const uint32_t la = pack_bf16(c0 ? s0[0] : sp[0], c0 ? s1[2] : s0[2]), lb = pack_bf16(c1 ? s0[1] : sp[1], c1 ? s1[3] : s0[3]);
        uint32_t mx = hmax2_bf(la, lb);
        mx = hmax2_bf(mx, __shfl_xor_sync(0xffffffffu, mx, 1));
        mx = hmax2_bf(mx, __shfl_xor_sync(0xffffffffu, mx, 2));
        const float C = 0.25f * 1.4426950408889634f;
        const float na = -C * bf_lo(mx), nb = -C * bf_hi(mx);
        const uint32_t pa = pack_bf16(ex2(fmaf(bf_lo(la), C, na)), ex2(fmaf(bf_lo(lb), C, na)));
        const uint32_t pb = pack_bf16(ex2(fmaf(bf_hi(la), C, nb)), ex2(fmaf(bf_hi(lb), C, nb)));
        float o0[4], o1[4], sm[4];
        mma16816z(o0, pa & ~mcur, 0u, pa & mcur, pb & ~mcur, H[8 + 2 * h], P[16 + 2 * h][0], Z);
        mma16816z(o1, pa & ~mcur, 0u, pa & mcur, pb & ~mcur, H[9 + 2 * h], P[17 + 2 * h][0], Z);
        mma1688(o0, 0u, pb & mcur, P[16 + 2 * h][1]);
        mma1688(o1, 0u, pb & mcur, P[17 + 2 * h][1]);
        mma1688z(sm, pa, pb, 0x3F803F80u, Z);
        dep |= __float_as_uint(o0[0]) | __float_as_uint(o1[0]);
        dep |= __float_as_uint(sm[0]);
        const float ia = rcp(sm[0]), ib = rcp(sm[2]);
        stsm4(rowaddr + (((2 * h + (mi >> 1)) ^ r8) << 4), pack_bf16(o0[0] * ia, o0[1] * ia), pack_bf16(o0[2] * ib, o0[3] * ib),
              pack_bf16(o1[0] * ia, o1[1] * ia), pack_bf16(o1[2] * ib, o1[3] * ib));
      }
      bar_arrive_after<13>(384, dep, Z[0]);
    }
    if (tid == 0) PROF(30);
    if (tid == 128) PROF(31);
    fence_async_smem();
    if (OWIN >= 0) bar_sync<8, 384>(); else if (wg) bar_sync<7, 128>(); else bar_sync<6, 128>();
    if ((tid & 127) == 0) {
      tma3_st(&mp.m[M_O3], sb + OFF_R1 + wg * 8192, ta * 64, tb >> 3, (tb & 7) * 128 + wg * 64);
      bulk_commit();
      bulk_wait0_read();
    }
    __syncwarp();
    if (OWIN >= 0 && !NOPAUSE) bar_arrive<14, 384>();
    if ((tid & 127) == 0) {
      mbar_arrive(sb + BAR_OST);
      bulk_wait0();
      red_relaxed(ctr + 32 * (32 + (tb & 7)), 1);
      if (tid == 0) PROF(21);
    }
    __syncwarp();
    if (wg == 0) {
      float ao[64];
      undef_regs(ao);
      if (XAT == 1) bar_sync<3, 256>();
      if (tid == 0) {
        mbar_wait(sb + BAR_OST, 0);
        if (XAT == 2) mbar_wait(sb + BAR_FLAG + 32, 0);
        mbar_expect_tx(sb + BAR_X, 16384);
        tma3(sb + OFF_R1, &mp.m[M_X2], sb + BAR_X, ta * 64, tb * 128, 0);
      }
      __syncwarp();
      if (XAT != 1) bar_sync<3, 256>();
      mbar_wait(full_bar(sb, N_OP), (N_OP >> 3) & 1);
      if (tid == 0) PROF(22);
#pragma unroll 1
      for (n = N_OP;; n++) {
        const uint32_t a = dlo(slot_addr(sb, n));
        wg_fence();
        wgmma_n128<1, 0>(ao, dsc(a), dsc(a + 512), n != N_OP);
        const uint32_t fast = mbar_test(full_bar(sb, n + 1), ((n + 1) >> 3) & 1) & (n != N_END - 1);
        wgmma_n128<1, 0>(ao, dsc(a + 128), dsc(a + 514), 1);
        wgmma_n128<1, 0>(ao, dsc(a + 256), dsc(a + 516), 1);
        wgmma_n128<1, 0>(ao, dsc(a + 384), dsc(a + 518), 1);
        wg_commit();
        if (fast) continue;
        if (n == N_END - 1) break;
        mbar_wait(full_bar(sb, n + 1), ((n + 1) >> 3) & 1);
      }
      uint32_t G[32], X[32];
      mbar_wait(sb + BAR_X, 0);
      const uint32_t xaddr = sb + OFF_R1 + ((mi >> 1) * 8 + r8) * 128 + (((2 * warp + (mi & 1)) ^ r8) << 4);
#pragma unroll
      for (int k = 0; k < 8; k++) ldsm4t(xaddr + k * 2048, X[4 * k], X[4 * k + 1], X[4 * k + 2], X[4 * k + 3]);
      bar_sync<4, 256>();
#pragma unroll
      for (int k = 0; k < 8; k++) ldsm4t(xaddr - 16384 + k * 2048, G[4 * k], G[4 * k + 1], G[4 * k + 2], G[4 * k + 3]);
      wg_wait<0>();
      fence_regs(ao);
      if (tid == 0) { mbar_arrive(sb + BAR_DONE); PROF(23); }
#pragma unroll
      for (int k = 0; k < 8; k++) {
        uint32_t o4[4];
#pragma unroll
        for (int q = 0; q < 4; q++)
          o4[q] = hadd2_bf(X[4 * k + q], hmul2_bf(pack_bf16(ao[8 * k + 2 * q], ao[8 * k + 2 * q + 1]), G[4 * k + q]));
        stsm4t(xaddr + k * 2048, o4[0], o4[1], o4[2], o4[3]);
        if ((k & 3) == 3) {
          fence_async_smem();
          bar_sync<6, 128>();
          if (tid == 0) {
            tma3_st(&mp.m[M_OUT], sb + OFF_R1 + (k >> 2) * 8192, ta * 64, tb * 128 + (k >> 2) * 64, 0);
            bulk_commit();
          }
        }
      }
      if (tid == 0) {
        if (role == 0) ctr[0] = ep + 1;
        bulk_wait0_read();
        PROF(24);
      }
    }
  }
}

typedef CUresult (*EncFn)(CUtensorMap*, CUtensorMapDataType, cuuint32_t, void*, const cuuint64_t*, const cuuint64_t*,
                          const cuuint32_t*, const cuuint32_t*, CUtensorMapInterleave, CUtensorMapSwizzle,
                          CUtensorMapL2promotion, CUtensorMapFloatOOBfill);

void enc(EncFn f, CUtensorMap* m, const void* p, cuuint64_t d0, cuuint64_t d1, cuuint64_t d2, cuuint64_t s1,
         cuuint64_t s2, cuuint32_t b0, cuuint32_t b1, cuuint32_t b2) {
  cuuint64_t gd[3] = {d0, d1, d2}, gs[2] = {s1, s2};
  cuuint32_t bd[3] = {b0, b1, b2}, es[3] = {1, 1, 1};
  f(m, CU_TENSOR_MAP_DATA_TYPE_BFLOAT16, 3, const_cast<void*>(p), gd, gs, bd, es, CU_TENSOR_MAP_INTERLEAVE_NONE,
    CU_TENSOR_MAP_SWIZZLE_128B, CU_TENSOR_MAP_L2_PROMOTION_L2_256B, CU_TENSOR_MAP_FLOAT_OOB_FILL_NONE);
}

}

extern "C" void kernel_launch(void* const* d_in, const int* in_sizes, int n_in, void* d_out, int out_size) {
  (void)in_sizes; (void)n_in; (void)out_size;
  const __nv_bfloat16* x = (const __nv_bfloat16*)d_in[0];
  const __nv_bfloat16* wqkv = (const __nv_bfloat16*)d_in[1];
  const __nv_bfloat16* wo = (const __nv_bfloat16*)d_in[2];
  const __nv_bfloat16* w1 = (const __nv_bfloat16*)d_in[4];
  const __nv_bfloat16* b1 = (const __nv_bfloat16*)d_in[5];
  const __nv_bfloat16* w2 = (const __nv_bfloat16*)d_in[6];
  const __nv_bfloat16* b2 = (const __nv_bfloat16*)d_in[7];

  void* fp = nullptr;
  cudaDriverEntryPointQueryResult qr;
  cudaGetDriverEntryPoint("cuTensorMapEncodeTiled", &fp, cudaEnableDefault, &qr);
  EncFn f = (EncFn)fp;
  Scratch* sc = nullptr;
  cudaGetSymbolAddress((void**)&sc, g_s);
  Maps mp;
  enc(f, &mp.m[M_X3], x, 512, 2, 1024, 1024, 2048, 64, 1, 128);
  enc(f, &mp.m[M_W3], wqkv, 512, 512, 3, 3072, 1024, 64, 64, 3);
  enc(f, &mp.m[M_H], sc->h, 512, 2048, 1, 1024, 1024 * 2048, 64, 64, 1);
  enc(f, &mp.m[M_W1], w1, 64, 2048, 28, 3584, 128, 64, 64, 2);
  enc(f, &mp.m[M_U], sc->u, 512, 1792, 1, 1024, 1024 * 1792, 64, 64, 1);
  enc(f, &mp.m[M_W2], w2, 64, 1792, 32, 4096, 128, 64, 64, 2);
  enc(f, &mp.m[M_WO], wo, 512, 512, 1, 1024, 1024 * 512, 64, 64, 1);
  enc(f, &mp.m[M_O2], sc->o, 512, 2048, 1, 1024, 1024 * 2048, 64, 128, 1);
  enc(f, &mp.m[M_O3], sc->o, 512, 2, 1024, 1024, 2048, 64, 1, 64);
  enc(f, &mp.m[M_X2], x, 512, 2048, 1, 1024, 1024 * 2048, 64, 128, 1);
  enc(f, &mp.m[M_OUT], d_out, 512, 2048, 1, 1024, 1024 * 2048, 64, 64, 1);
  for (int sm = 0; sm < 160; sm++) {
    int gpc, idx;
    if (sm < 64) { gpc = (sm >> 1) & 7; idx = (sm >> 4) * 2 + (sm & 1); }
    else if (sm < 120) { const int tp = (sm - 64) >> 1; gpc = 1 + tp % 7; idx = 8 + (tp / 7) * 2 + (sm & 1); }
    else { gpc = 0; idx = sm - 116; }
    const int a = (gpc & 1) * 4 + (idx & 3), b = (gpc >> 1) * 4 + (idx >> 2);
    mp.role[sm] = sm >= 120 && sm < 124 ? (uint8_t)(132 + sm) : (uint8_t)(b * 8 + a);
  }
  cudaFuncSetAttribute(fused_kernel, cudaFuncAttributeMaxDynamicSharedMemorySize, SMEM_BYTES);
  fused_kernel<<<132, 512, SMEM_BYTES, cudaStreamPerThread>>>(mp, x, wqkv, b1, b2);
}
```
